```python
import torch

def _softmax(x, axis=-1):
    return torch.softmax(x, dim=axis)
def _gelu(x):
    return torch.nn.functional.gelu(x, approximate="tanh")
def _silu(x):
    return torch.nn.functional.silu(x)
def _sigmoid(x):
    return torch.sigmoid(x)
def _layernorm(x, axis=-1, eps=1e-5):
    m = x.mean(dim=axis, keepdim=True)
    v = x.var(dim=axis, keepdim=True, unbiased=False)
    return (x - m) / torch.sqrt(v + eps)
def _scatter_add(tgt, idx, src, axis=0):
    return tgt.clone().index_add_(axis, idx, src)
def _segment_sum(src, seg, n):
    out = torch.zeros((n,) + src.shape[1:], dtype=src.dtype)
    return out.index_add_(0, seg, src)
def _pad(x, pw):
    flat = tuple(v for pair in reversed(pw) for v in pair)
    return torch.nn.functional.pad(x, flat)

kernel_name = 'gated_mix__linear_attn_block__glu_gated_bilinear__prompt'

def setup_inputs():

    _w = (lambda a: (lambda t: t.to(torch.bfloat16) if t.is_floating_point() else t)(torch.as_tensor(a)))
    def _A_setup():
        B, S, D = 1, 2048, 512
        return {
            "x": _w((lambda *s: torch.randn(*s, dtype=torch.bfloat16) * 0.05)(B, S, D)),
            "wqkv": _w((lambda *s: torch.randn(*s, dtype=torch.bfloat16) * 0.8)(D, 3 * D)),
            "wo": _w((lambda *s: torch.randn(*s, dtype=torch.bfloat16) * 0.05)(D, D)),
        }
    _A_in = _A_setup()

    def _B_setup():
        B, S, D, F = 1, 2048, 512, 1792
        return {
            "x": _w((lambda *s: torch.randn(*s, dtype=torch.bfloat16) * 0.05)(B, S, D)),
            "w_gate": _w((lambda *s: torch.randn(*s, dtype=torch.bfloat16) * 1.6)(D, F) * (D ** -0.5)),
            "w_up": _w((lambda *s: torch.randn(*s, dtype=torch.bfloat16) * 1.6)(D, F) * (D ** -0.5)),
            "w_down": _w((lambda *s: torch.randn(*s, dtype=torch.bfloat16) * 1.6)(F, D) * (F ** -0.5)),
        }
    _B_in = _B_setup()

    return {
        "A_x": _A_in["x"],
        "A_wqkv": _A_in["wqkv"],
        "A_wo": _A_in["wo"],
        "B_x": _B_in["x"],
        "B_w_gate": _B_in["w_gate"],
        "B_w_up": _B_in["w_up"],
        "B_w_down": _B_in["w_down"],
        "gate_w": _w((lambda *s: torch.randn(*s, dtype=torch.bfloat16) * 0.05)(512) * 16.0),
    }

def reference(A_x, A_wqkv, A_wo, B_x, B_w_gate, B_w_up, B_w_down, gate_w):
    def _A_ref(x, wqkv, wo):
        B, S, D = x.shape
        H = 32; Dh = D // H
        qkv = (lambda x, *d: x.permute(*d))((x @ wqkv).reshape(B, S, 3, H, Dh), 2, 0, 3, 1, 4)
        q, k, v = qkv[0], qkv[1], qkv[2]
        phi = lambda t: torch.where(t > 0, t + 1, torch.exp(t)) + 1e-6
        pq, pk = phi(q), phi(k)
        kv = torch.einsum("bhsd,bhse->bhde", pk, v)
        z = torch.einsum("bhsd->bhd", pk)
        num = torch.einsum("bhqd,bhde->bhqe", pq, kv)
        den = torch.einsum("bhqd,bhd->bhq", pq, z)[..., None] + 1e-6
        o = num / den
        return (lambda x, *d: x.permute(*d))(o, 0, 2, 1, 3).reshape(B, S, D) @ wo

    def _B_ref(x, w_gate, w_up, w_down):
        g = torch.einsum("bsd,df->bsf", x, w_gate)
        u = torch.einsum("bsd,df->bsf", x, w_up)
        h = g * u
        return torch.einsum("bsf,fd->bsd", h, w_down)

    x = A_x
    g = _sigmoid((x * gate_w).sum(-1, keepdims=True))
    a = _A_ref(x, A_wqkv, A_wo)
    b = _B_ref(x, B_w_gate, B_w_up, B_w_down)
    return g * a + (1 - g) * b
```

```cpp
#include <cuda_runtime.h>
#include <cuda_bf16.h>
#include <cuda.h>
#include <stdint.h>
#include <stdio.h>

namespace {

constexpr int SEQ = 2048, DM = 512, FF = 1792;
constexpr int NKB2 = 36;
constexpr uint32_t BLK = 16384;

constexpr uint32_t OFF_X = 0;
#define NSLOT 4
constexpr uint32_t OFF_B = 131072;
constexpr uint32_t OFF_STG = 196608;
constexpr uint32_t OFF_ONES = 229376;
constexpr uint32_t OFF_G = 231424;
constexpr uint32_t OFF_BAR = 231936;
constexpr uint32_t XFULL = OFF_BAR, BFULL = XFULL + 64, BEMPTY = BFULL + 64, GFULL = BEMPTY + 64,
                   GEMPTY = GFULL + 48, GREADY = GEMPTY + 48, EREADY = GREADY + 8, KVREADY = EREADY + 8,
                   STGFREE = KVREADY + 8, TXOK = STGFREE + 8, RXFULL = TXOK + 8, OFF_EPOCH = RXFULL + 32;
constexpr uint32_t SMEM_BYTES = OFF_EPOCH + 16;

constexpr int BAR_ORDER0 = 1, BAR_ORDER1 = 2, BAR_WG0 = 3, BAR_TAIL = 4, BAR_STORE = 5;
#define SPLIT_SKEW 1
#define TAIL_LEAD 5

__device__ __align__(1024) uint8_t g_hbuf[16 * NKB2 * BLK];
__device__ __align__(128) uint32_t g_flags[16 * 64];
__device__ uint32_t g_kvcnt[8 * 32];
__device__ __align__(128) float g_kvacc[2][32][272];
__device__ unsigned long long g_gate[SEQ];

#define TS(i) do {} while (0)
#define TSG(i) do {} while (0)

constexpr uint32_t SPIN_LIMIT = 1u << 24;

__device__ __forceinline__ uint32_t smem_u32(const void* p) { return (uint32_t)__cvta_generic_to_shared(p); }
__device__ __forceinline__ void mbar_init(uint32_t bar, uint32_t cnt) {
    asm volatile("mbarrier.init.shared::cta.b64 [%0], %1;" ::"r"(bar), "r"(cnt) : "memory");
}
__device__ __forceinline__ void mbar_expect_tx(uint32_t bar, uint32_t bytes) {
    asm volatile("mbarrier.arrive.expect_tx.shared::cta.b64 _, [%0], %1;" ::"r"(bar), "r"(bytes) : "memory");
}
__device__ __forceinline__ void mbar_arrive(uint32_t bar) {
    asm volatile("mbarrier.arrive.shared::cta.b64 _, [%0];" ::"r"(bar) : "memory");
}
__device__ __forceinline__ uint32_t mapa(uint32_t addr, uint32_t cta) {
    uint32_t r;
    asm volatile("mapa.shared::cluster.u32 %0, %1, %2;" : "=r"(r) : "r"(addr), "r"(cta));
    return r;
}
__device__ __forceinline__ void mbar_arrive_remote(uint32_t remote_bar) {
    asm volatile("mbarrier.arrive.shared::cluster.b64 _, [%0];" ::"r"(remote_bar) : "memory");
}
__device__ __forceinline__ void mbar_wait(uint32_t bar, uint32_t parity) {
    asm volatile("{\n.reg .pred p;\n.reg .u32 n;\nmov.u32 n, 0;\nWAIT_LOOP:\n"
                 "mbarrier.try_wait.parity.shared::cta.b64 p, [%0], %1;\n@p bra WAIT_DONE;\n"
                 "add.u32 n, n, 1;\nsetp.lt.u32 p, n, 0x400000;\n@p bra WAIT_LOOP;\ntrap;\nWAIT_DONE:\n}" ::"r"(bar), "r"(parity) : "memory");
}
__device__ __forceinline__ void bar_sync(int id, int n) { asm volatile("bar.sync %0, %1;" ::"r"(id), "r"(n) : "memory"); }
__device__ __forceinline__ void bar_arrive(int id, int n) { asm volatile("bar.arrive %0, %1;" ::"r"(id), "r"(n) : "memory"); }

__device__ __forceinline__ void tma_load_2d(uint32_t dst, const CUtensorMap* tm, int c0, int c1, uint32_t bar) {
    asm volatile("cp.async.bulk.tensor.2d.shared::cluster.global.mbarrier::complete_tx::bytes [%0], [%1, {%3, %4}], [%2];"
                 ::"r"(dst), "l"(tm), "r"(bar), "r"(c0), "r"(c1) : "memory");
}
__device__ __forceinline__ void tma_load_3d(uint32_t dst, const CUtensorMap* tm, int c0, int c1, int c2, uint32_t bar) {
    asm volatile("cp.async.bulk.tensor.3d.shared::cluster.global.mbarrier::complete_tx::bytes [%0], [%1, {%3, %4, %5}], [%2];"
                 ::"r"(dst), "l"(tm), "r"(bar), "r"(c0), "r"(c1), "r"(c2) : "memory");
}
__device__ __forceinline__ void tma_prefetch_2d(const CUtensorMap* tm, int c0, int c1) {
    asm volatile("cp.async.bulk.prefetch.tensor.2d.L2.global.tile [%0, {%1, %2}];" ::"l"(tm), "r"(c0), "r"(c1) : "memory");
}
__device__ __forceinline__ void tma_prefetch_3d(const CUtensorMap* tm, int c0, int c1, int c2) {
    asm volatile("cp.async.bulk.prefetch.tensor.3d.L2.global.tile [%0, {%1, %2, %3}];" ::"l"(tm), "r"(c0), "r"(c1), "r"(c2) : "memory");
}
__device__ __forceinline__ void tma_store_3d(const CUtensorMap* tm, uint32_t src, int c0, int c1, int c2) {
    asm volatile("cp.async.bulk.tensor.3d.global.shared::cta.bulk_group [%0, {%2, %3, %4}], [%1];"
                 ::"l"(tm), "r"(src), "r"(c0), "r"(c1), "r"(c2) : "memory");
}
__device__ __forceinline__ void bulk_load(uint32_t dst, const void* src, uint32_t bytes, uint32_t bar) {
    asm volatile("cp.async.bulk.shared::cluster.global.mbarrier::complete_tx::bytes [%0], [%1], %2, [%3];"
                 ::"r"(dst), "l"(src), "r"(bytes), "r"(bar) : "memory");
}
__device__ __forceinline__ void bulk_store(void* dst, uint32_t src, uint32_t bytes) {
    asm volatile("cp.async.bulk.global.shared::cta.bulk_group [%0], [%1], %2;" ::"l"(dst), "r"(src), "r"(bytes) : "memory");
}
__device__ __forceinline__ void prefetch_tmap(const CUtensorMap* tm) {
    asm volatile("prefetch.tensormap [%0];" ::"l"(tm) : "memory");
}
__device__ __forceinline__ uint32_t ld_acquire(const uint32_t* p) {
    uint32_t v;
    asm volatile("ld.acquire.gpu.global.u32 %0, [%1];" : "=r"(v) : "l"(p) : "memory");
    return v;
}
__device__ __forceinline__ uint32_t ld_relaxed(const uint32_t* p) {
    uint32_t v;
    asm volatile("ld.relaxed.gpu.global.u32 %0, [%1];" : "=r"(v) : "l"(p) : "memory");
    return v;
}
__device__ __forceinline__ void st_relaxed(uint32_t* p, uint32_t v) {
    asm volatile("st.relaxed.gpu.global.u32 [%0], %1;" ::"l"(p), "r"(v) : "memory");
}
__device__ __forceinline__ void red_add_v4(float* p, float a, float b, float c, float d) {
    asm volatile("red.relaxed.gpu.global.add.v4.f32 [%0], {%1, %2, %3, %4};" ::"l"(p), "f"(a), "f"(b), "f"(c), "f"(d) : "memory");
}
__device__ __forceinline__ float4 ld_cg4(const float* p) {
    float4 v;
    asm volatile("ld.relaxed.gpu.global.v4.f32 {%0, %1, %2, %3}, [%4];" : "=f"(v.x), "=f"(v.y), "=f"(v.z), "=f"(v.w) : "l"(p) : "memory");
    return v;
}
__device__ __forceinline__ void wgmma_fence() { asm volatile("wgmma.fence.sync.aligned;" ::: "memory"); }
__device__ __forceinline__ void wgmma_commit() { asm volatile("wgmma.commit_group.sync.aligned;" ::: "memory"); }
template <int N> __device__ __forceinline__ void wgmma_wait() { asm volatile("wgmma.wait_group.sync.aligned %0;" ::"n"(N) : "memory"); }

__device__ __forceinline__ uint64_t desc_a(uint32_t addr) {
    return (uint64_t)(((addr & 0x3FFFF) >> 4) | (1u << 16)) | ((uint64_t)(64u | (1u << 30)) << 32);
}
__device__ __forceinline__ uint64_t desc_b(uint32_t addr, uint32_t lbo = 8192) {
    return (uint64_t)(((addr & 0x3FFFF) >> 4) | ((lbo >> 4) << 16)) | ((uint64_t)(64u | (1u << 30)) << 32);
}
#define ACC8(a, o) "+f"(a[o + 0]), "+f"(a[o + 1]), "+f"(a[o + 2]), "+f"(a[o + 3]), "+f"(a[o + 4]), "+f"(a[o + 5]), "+f"(a[o + 6]), "+f"(a[o + 7])
__device__ __forceinline__ void wgmma_n128(float (&d)[64], uint64_t da, uint64_t db) {
    asm volatile("wgmma.mma_async.sync.aligned.m64n128k16.f32.bf16.bf16 "
                 "{%0,%1,%2,%3,%4,%5,%6,%7,%8,%9,%10,%11,%12,%13,%14,%15,%16,%17,%18,%19,%20,%21,%22,%23,%24,%25,%26,%27,%28,%29,%30,%31,"
                 "%32,%33,%34,%35,%36,%37,%38,%39,%40,%41,%42,%43,%44,%45,%46,%47,%48,%49,%50,%51,%52,%53,%54,%55,%56,%57,%58,%59,%60,%61,%62,%63},"
                 " %64, %65, 1, 1, 1, 0, 1;"
                 : ACC8(d, 0), ACC8(d, 8), ACC8(d, 16), ACC8(d, 24), ACC8(d, 32), ACC8(d, 40), ACC8(d, 48), ACC8(d, 56)
                 : "l"(da), "l"(db));
}
#define OUT8(a, o) "=f"(a[o + 0]), "=f"(a[o + 1]), "=f"(a[o + 2]), "=f"(a[o + 3]), "=f"(a[o + 4]), "=f"(a[o + 5]), "=f"(a[o + 6]), "=f"(a[o + 7])
__device__ __forceinline__ void wgmma_n128_first(float (&d)[64], uint64_t da, uint64_t db) {
    asm volatile("wgmma.mma_async.sync.aligned.m64n128k16.f32.bf16.bf16 "
                 "{%0,%1,%2,%3,%4,%5,%6,%7,%8,%9,%10,%11,%12,%13,%14,%15,%16,%17,%18,%19,%20,%21,%22,%23,%24,%25,%26,%27,%28,%29,%30,%31,"
                 "%32,%33,%34,%35,%36,%37,%38,%39,%40,%41,%42,%43,%44,%45,%46,%47,%48,%49,%50,%51,%52,%53,%54,%55,%56,%57,%58,%59,%60,%61,%62,%63},"
                 " %64, %65, 0, 1, 1, 0, 1;"
                 : OUT8(d, 0), OUT8(d, 8), OUT8(d, 16), OUT8(d, 24), OUT8(d, 32), OUT8(d, 40), OUT8(d, 48), OUT8(d, 56)
                 : "l"(da), "l"(db));
}
__device__ __forceinline__ void wgmma_n72_tt(float (&d)[36], uint64_t da, uint64_t db) {
    asm volatile("wgmma.mma_async.sync.aligned.m64n72k16.f32.bf16.bf16 "
                 "{%0,%1,%2,%3,%4,%5,%6,%7,%8,%9,%10,%11,%12,%13,%14,%15,%16,%17,%18,%19,%20,%21,%22,%23,%24,%25,%26,%27,%28,%29,%30,%31,"
                 "%32,%33,%34,%35}, %36, %37, 1, 1, 1, 1, 1;"
                 : ACC8(d, 0), ACC8(d, 8), ACC8(d, 16), ACC8(d, 24), "+f"(d[32]), "+f"(d[33]), "+f"(d[34]), "+f"(d[35])
                 : "l"(da), "l"(db));
}
__device__ __forceinline__ void wgmma_n24_rs(float (&d)[12], const uint32_t (&a)[4], uint64_t db) {
    asm volatile("wgmma.mma_async.sync.aligned.m64n24k16.f32.bf16.bf16 "
                 "{%0,%1,%2,%3,%4,%5,%6,%7,%8,%9,%10,%11}, {%12,%13,%14,%15}, %16, 0, 1, 1, 1;"
                 : "=f"(d[0]), "=f"(d[1]), "=f"(d[2]), "=f"(d[3]), "=f"(d[4]), "=f"(d[5]), "=f"(d[6]), "=f"(d[7]),
                   "=f"(d[8]), "=f"(d[9]), "=f"(d[10]), "=f"(d[11])
                 : "r"(a[0]), "r"(a[1]), "r"(a[2]), "r"(a[3]), "l"(db));
}
template <int N> __device__ __forceinline__ void fence_regs(float (&d)[N]) {
#pragma unroll
    for (int i = 0; i < N; i++) asm volatile("" : "+f"(d[i])::"memory");
}
__device__ __forceinline__ void stsm_x4(uint32_t addr, uint32_t r0, uint32_t r1, uint32_t r2, uint32_t r3) {
    asm volatile("stmatrix.sync.aligned.m8n8.x4.shared.b16 [%0], {%1,%2,%3,%4};" ::"r"(addr), "r"(r0), "r"(r1), "r"(r2), "r"(r3) : "memory");
}
__device__ __forceinline__ uint32_t pack2(float lo, float hi) {
    uint32_t r;
    asm("cvt.rn.bf16x2.f32 %0, %1, %2;" : "=r"(r) : "f"(hi), "f"(lo));
    return r;
}
__device__ __forceinline__ float lds_f32(uint32_t addr) {
    float v;
    asm volatile("ld.shared.f32 %0, [%1];" : "=f"(v) : "r"(addr) : "memory");
    return v;
}
__device__ __forceinline__ float ex2(float x) {
    float y;
    asm("ex2.approx.ftz.f32 %0, %1;" : "=f"(y) : "f"(x));
    return y;
}
__device__ __forceinline__ float rcp(float x) {
    float y;
    asm("rcp.approx.ftz.f32 %0, %1;" : "=f"(y) : "f"(x));
    return y;
}
__device__ __forceinline__ uint32_t hmul2(uint32_t a, uint32_t b) {
    uint32_t r;
    asm("mul.rn.bf16x2 %0, %1, %2;" : "=r"(r) : "r"(a), "r"(b));
    return r;
}
__device__ __forceinline__ uint32_t phi2(float t0, float t1) {
    uint32_t e = pack2(ex2(t0 * 1.4426950408889634f), ex2(t1 * 1.4426950408889634f));
    uint32_t t = pack2(t0, t1), r;
    asm("min.bf16x2 %0, %0, %1;" : "+r"(e) : "r"(0x3f803f80u));
    asm("max.bf16x2 %0, %0, %1;" : "+r"(t) : "r"(0x35863586u));
    asm("add.rn.bf16x2 %0, %1, %2;" : "=r"(r) : "r"(t), "r"(e));
    return r;
}
__device__ __forceinline__ bool elect_one() {
    uint32_t pred;
    asm volatile("{\n.reg .pred p;\nelect.sync _|p, 0xffffffff;\nselp.u32 %0, 1, 0, p;\n}" : "=r"(pred));
    return pred != 0;
}

struct Params {
    CUtensorMap x, qkv, wg, wu, wd, wo, out;
    const __nv_bfloat16* gate_w;
    const __nv_bfloat16* xp;
};

__device__ __forceinline__ void slot_weights(const Params& p, int slot, int ct, int rank, const CUtensorMap*& m0,
                                             const CUtensorMap*& m1, int& c0, int& c1) {
    const int j = 2 * ct + rank;
    if (slot == 0) { m0 = m1 = &p.qkv; c0 = 512 + 64 * j; c1 = 1024 + 64 * j; }
    else if (slot == 2 && rank == 0) { m0 = m1 = &p.qkv; c0 = 128 * ct; c1 = c0 + 64; }
    else {
        const int h = slot == 1 ? j : slot == 2 ? 8 + ct : slot == 3 ? 12 + j : 20 + j;
        m0 = &p.wg; m1 = &p.wu; c0 = c1 = 64 * h;
    }
}
__device__ __forceinline__ constexpr int gemm2_block_k(int k, int rank) {
    return k == 0 ? 0 : k < 5 ? 2 * (k - 1) + rank : k < 7 ? 8 + 2 * rank + (k - 5) : k < 11 ? 28 + 4 * rank + (k - 7)
         : k < 15 ? 12 + 2 * (k - 11) + rank : k < 19 ? 20 + 2 * (k - 15) + rank : 0;
}
__device__ __forceinline__ constexpr int gemm2_k0(int rank) { return SPLIT_SKEW ? 2 - 2 * rank : 1; }
__device__ __forceinline__ constexpr int gemm2_n(int rank) { return SPLIT_SKEW ? 17 + 2 * rank : 18; }
__device__ __forceinline__ constexpr uint32_t gstage_off(int s) { return (uint32_t)(s == 3 ? 4 : s == 4 ? 3 : s) * 32768u; }

__global__ void __cluster_dims__(2, 1, 1) __launch_bounds__(384, 1)
fused_kernel(const __grid_constant__ Params p) {
    extern __shared__ __align__(1024) uint8_t smem_raw[];
    const uint32_t sb = __shfl_sync(0xffffffffu, smem_u32(smem_raw), 0);
    const int warp = __shfl_sync(0xffffffffu, threadIdx.x >> 5, 0), lane = threadIdx.x & 31;
    const int rank = blockIdx.x & 1;
    int rb, ct;
    {
        const int c = blockIdx.x >> 1;
        if (c < 4) { rb = 15; ct = c; }
        else if (c < 36) { rb = (c - 4) & 7; ct = (c - 4) >> 3; }
        else { rb = 8 + (c - 36) % 7; ct = (c - 36) / 7; }
    }
    const int j = 2 * ct + rank;

    if (warp == 8 && elect_one()) {
        TS(0); TSG(62);
        for (int i = 0; i < 16; i++) mbar_init(sb + XFULL + 8 * i, 1);
        asm volatile("fence.proxy.async.shared::cta;" ::: "memory");
        for (int k = 0; k < 4; k++) {
            mbar_expect_tx(sb + XFULL + 8 * k, BLK);
            tma_load_2d(sb + OFF_X + k * BLK, &p.x, 64 * k, 128 * rb, sb + XFULL + 8 * k);
            mbar_expect_tx(sb + BFULL + 8 * k, BLK);
            tma_load_2d(sb + OFF_B + k * BLK, &p.qkv, 512 + 64 * j, 64 * k, sb + BFULL + 8 * k);
            tma_load_2d(sb + OFF_B + k * BLK + 8192, &p.qkv, 1024 + 64 * j, 64 * k, sb + BFULL + 8 * k);
        }
        if (rb < 8) tma_prefetch_2d(&p.qkv, 512 + 512 * (rb & 1) + 64 * j, 256 + 64 * (rb >> 1));
        for (int k = 4; k < 8; k++) {
            mbar_expect_tx(sb + XFULL + 8 * k, BLK);
            tma_load_2d(sb + OFF_X + k * BLK, &p.x, 64 * k, 128 * rb, sb + XFULL + 8 * k);
        }
        TS(1);
    } else if (warp == 9 && elect_one()) {
        if (sb & 1023) __trap();
        for (int i = 0; i < 8; i++) mbar_init(sb + BEMPTY + 8 * i, 4);
        for (int i = 0; i < 6; i++) { mbar_init(sb + GFULL + 8 * i, 2); mbar_init(sb + GEMPTY + 8 * i, 8); }
        mbar_init(sb + GREADY, 2); mbar_init(sb + EREADY, 1); mbar_init(sb + KVREADY, 2);
        mbar_init(sb + STGFREE, 1); mbar_init(sb + TXOK, 1);
        for (int i = 0; i < 4; i++) { mbar_init(sb + RXFULL + 8 * i, 1); mbar_expect_tx(sb + RXFULL + 8 * i, 8192); }
        asm volatile("st.shared.u32 [%0], %1;" ::"r"(sb + OFF_EPOCH + 4), "r"(0u) : "memory");
        asm volatile("fence.mbarrier_init.release.cluster;" ::: "memory");
    }
    if (threadIdx.x < 128) {
        asm volatile("st.shared.v4.u32 [%0], {%1,%1,%1,%1};" ::"r"(sb + OFF_ONES + threadIdx.x * 16), "r"(0x3f803f80u) : "memory");
        asm volatile("fence.proxy.async.shared::cta;" ::: "memory");
    }
    __syncthreads();
    asm volatile("barrier.cluster.arrive.relaxed.aligned;" ::: "memory");

    if (warp >= 8) {
        asm volatile("setmaxnreg.dec.sync.aligned.u32 40;");
        if (warp == 8) {
            if (elect_one()) {
                uint32_t s = 4 % NSLOT, ph = (4 / NSLOT) ^ 1;
#pragma unroll 1
                for (int slot = 0; slot < 5; slot++) {
                    const CUtensorMap *m0, *m1; int c0, c1;
                    slot_weights(p, slot, ct, rank, m0, m1, c0, c1);
#pragma unroll 4
                    for (int kb = slot == 0 ? 4 : 0; kb < 8; kb++) {
                        mbar_wait(sb + BEMPTY + 8 * s, ph);
                        mbar_expect_tx(sb + BFULL + 8 * s, BLK);
                        tma_load_2d(sb + OFF_B + s * BLK, m0, c0, 64 * kb, sb + BFULL + 8 * s);
                        tma_load_2d(sb + OFF_B + s * BLK + 8192, m1, c1, 64 * kb, sb + BFULL + 8 * s);
                        if (++s == NSLOT) { s = 0; ph ^= 1; }
                    }
                }
                TS(38);
#pragma unroll
                for (int i = 0; i < 19; i++) {
                    if (i < gemm2_n(rank)) {
                        const int s = i % 6;
                        const int blk = rank ? gemm2_block_k(i + gemm2_k0(1), 1) : gemm2_block_k(i + gemm2_k0(0), 0);
                        mbar_wait(sb + GEMPTY + 8 * s, (i / 6) & 1);
                        mbar_expect_tx(sb + GFULL + 8 * s, BLK);
                        tma_load_3d(sb + gstage_off(s) + BLK, blk < 28 ? &p.wd : &p.wo, 0, 64 * (blk < 28 ? blk : blk - 28), 2 * ct, sb + GFULL + 8 * s);
                    }
                }
            }
        } else if (warp == 9) {
            if (elect_one()) {
                {
                    const CUtensorMap *m0, *m1; int c0, c1;
                    slot_weights(p, 1, ct, rank, m0, m1, c0, c1);
                    tma_prefetch_2d((rb & 1) ? m1 : m0, (rb & 1) ? c1 : c0, 64 * (rb >> 1));
                }
                asm volatile("st.shared.u32 [%0], %1;" ::"r"(sb + OFF_EPOCH), "r"(ld_relaxed(g_kvcnt + 32 * j) >> 4) : "memory");
                mbar_arrive(sb + EREADY);
                mbar_wait(sb + XFULL + 8 * 3, 0);
                for (int slot = 2; slot < 5; slot++) {
                    const CUtensorMap *m0, *m1; int c0, c1;
                    slot_weights(p, slot, ct, rank, m0, m1, c0, c1);
                    tma_prefetch_2d((rb & 1) ? m1 : m0, (rb & 1) ? c1 : c0, 64 * (rb >> 1));
                }
                for (int i = rb; i < 18; i += 16) {
                    const int blk = gemm2_block_k(i + 1, rank);
                    if (blk < 28) tma_prefetch_3d(&p.wd, 0, 64 * blk, 2 * ct);
                    else tma_prefetch_3d(&p.wo, 0, 64 * (blk - 28), 2 * ct);
                }
                prefetch_tmap(&p.out);
            }
            __syncwarp();
            uint32_t epoch;
            asm volatile("ld.shared.u32 %0, [%1];" : "=r"(epoch) : "r"(sb + OFF_EPOCH) : "memory");
            if (lane < 17) reinterpret_cast<float4*>(&g_kvacc[(epoch + 1) & 1][0][0])[blockIdx.x * 17 + lane] = make_float4(0.f, 0.f, 0.f, 0.f);
            asm volatile("barrier.cluster.wait.aligned;" ::: "memory");
#pragma unroll 1
            for (int slot = 0; slot < 5; slot++) {
                bar_sync(BAR_STORE, 160);
                if (elect_one()) {
                    if (slot == 0) {
                        asm volatile("fence.acq_rel.gpu;" ::: "memory");
                        asm volatile("red.relaxed.gpu.global.add.u32 [%0], %1;" ::"l"(g_kvcnt + 32 * j), "r"(1u) : "memory");
                        mbar_arrive(sb + STGFREE);
                    } else {
                        const bool isq = (slot == 2 && rank == 0);
                        const int blk = isq ? 28 + 2 * ct : slot == 1 ? j : slot == 2 ? 8 + ct : slot == 3 ? 12 + j : 20 + j;
                        bulk_store(g_hbuf + (size_t)(rb * NKB2 + blk) * BLK, sb + OFF_STG, isq ? 2 * BLK : BLK);
                        asm volatile("cp.async.bulk.commit_group;" ::: "memory");
                        asm volatile("cp.async.bulk.wait_group 0;" ::: "memory");
                        int pos = slot == 2 ? (ct >> 1) * 32 + (isq ? 7 + 2 * (ct & 1) : 5 + (ct & 1))
                                            : rank * 32 + ct + (slot == 1 ? 1 : slot == 3 ? 11 : 15);
                        if (SPLIT_SKEW && blk == 0) pos = 32;
                        st_relaxed(g_flags + rb * 64 + pos, epoch + 1);
                        if (isq) st_relaxed(g_flags + rb * 64 + pos + 1, epoch + 1);
                        if (slot < 4) mbar_arrive(sb + STGFREE);
                        else mbar_arrive_remote(mapa(sb + TXOK, rank ^ 1));
                    }
                    TS(30 + slot);
                }
                __syncwarp();
            }
        } else {
            mbar_wait(sb + EREADY, 0);
            uint32_t epoch;
            asm volatile("ld.shared.u32 %0, [%1];" : "=r"(epoch) : "r"(sb + OFF_EPOCH) : "memory");
            {
                const int r = 64 * (warp - 10) + lane;
                unsigned long long e0, e1;
                uint32_t n = 0;
                do {
                    asm volatile("ld.relaxed.gpu.global.u64 %0, [%1];" : "=l"(e0) : "l"(g_gate + 128 * rb + r) : "memory");
                    asm volatile("ld.relaxed.gpu.global.u64 %0, [%1];" : "=l"(e1) : "l"(g_gate + 128 * rb + r + 32) : "memory");
                    if (++n > SPIN_LIMIT) __trap();
                } while (!__all_sync(0xffffffffu, (uint32_t)(e0 >> 32) == epoch + 1 && (uint32_t)(e1 >> 32) == epoch + 1));
                asm volatile("st.shared.u32 [%0], %1;" ::"r"(sb + OFF_G + 4 * r), "r"((uint32_t)e0) : "memory");
                asm volatile("st.shared.u32 [%0], %1;" ::"r"(sb + OFF_G + 4 * r + 128), "r"((uint32_t)e1) : "memory");
                __syncwarp();
                if (lane == 0) { mbar_arrive(sb + GREADY); if (warp == 10) TS(36); }
            }
            if (rank == 0) {
                const uint32_t target = (epoch + 1) << 4;
                uint32_t n = 0;
                while (!__all_sync(0xffffffffu, (int32_t)(ld_acquire(g_kvcnt + 32 * (j + (lane & 1))) - target) >= 0)) {
                    if (++n > SPIN_LIMIT) __trap();
                }
                __syncwarp();
                const int h0 = (warp - 10) * 4;
                const float* src = &g_kvacc[epoch & 1][8 * ct + h0][0];
#pragma unroll 2
                for (int h = 0; h < 4; h++) {
                    const float4 u0 = ld_cg4(src + h * 272 + lane * 8), u1 = ld_cg4(src + h * 272 + lane * 8 + 4);
                    const float za = __uint_as_float(ld_relaxed(reinterpret_cast<const uint32_t*>(src + h * 272 + 256 + (lane >> 2))));
                    const float zb = __uint_as_float(ld_relaxed(reinterpret_cast<const uint32_t*>(src + h * 272 + 264 + (lane >> 2))));
                    const uint32_t d = sb + OFF_STG + BLK + (h0 + h) * 768 + lane * 4;
                    asm volatile("st.shared.u32 [%0], %1;" ::"r"(d), "r"(pack2(u0.x, u0.y)) : "memory");
                    asm volatile("st.shared.u32 [%0], %1;" ::"r"(d + 128), "r"(pack2(u0.z, u0.w)) : "memory");
                    asm volatile("st.shared.u32 [%0], %1;" ::"r"(d + 256), "r"(pack2(u1.x, u1.y)) : "memory");
                    asm volatile("st.shared.u32 [%0], %1;" ::"r"(d + 384), "r"(pack2(u1.z, u1.w)) : "memory");
                    asm volatile("st.shared.u32 [%0], %1;" ::"r"(d + 512), "r"(pack2(za, za)) : "memory");
                    asm volatile("st.shared.u32 [%0], %1;" ::"r"(d + 640), "r"(pack2(zb, zb)) : "memory");
                }
                asm volatile("fence.proxy.async.shared::cta;" ::: "memory");
                __syncwarp();
                if (lane == 0) { mbar_arrive(sb + KVREADY); if (warp == 10) TS(37); }
            }
            if (warp == 11) {
                const uint32_t* fl = g_flags + rb * 64 + rank * 32 + gemm2_k0(rank) + lane;
                const uint32_t full = (1u << gemm2_n(rank)) - 1;
                uint32_t ready = 0, n = 0;
                while (ready != full) {
                    const uint32_t v = lane < gemm2_n(rank) ? ld_acquire(fl) : 0;
                    const uint32_t now = __ballot_sync(0xffffffffu, v == epoch + 1) & full;
                    if (now != ready) {
                        ready = now;
                        __syncwarp();
                        if (lane == 0) asm volatile("st.release.cta.shared.u32 [%0], %1;" ::"r"(sb + OFF_EPOCH + 4), "r"(__ffs(~now) - 1) : "memory");
                    } else {
                        __nanosleep(100);
                    }
                    if (++n > SPIN_LIMIT) __trap();
                }
            } else if (elect_one()) {
                const uint8_t* hb = g_hbuf + (size_t)rb * NKB2 * BLK;
                uint32_t have = 0;
#pragma unroll
                for (int i = 0; i < 19; i++) {
                    if (i < gemm2_n(rank)) {
                        const int s = i % 6;
                        mbar_wait(sb + GEMPTY + 8 * s, (i / 6) & 1);
                        uint32_t n = 0;
                        while (have <= i) {
                            asm volatile("ld.acquire.cta.shared.u32 %0, [%1];" : "=r"(have) : "r"(sb + OFF_EPOCH + 4) : "memory");
                            if (++n > (SPIN_LIMIT << 4)) __trap();
                        }
                        asm volatile("fence.proxy.async.global;" ::: "memory");
                        mbar_expect_tx(sb + GFULL + 8 * s, BLK);
                        const int blk = rank ? gemm2_block_k(i + gemm2_k0(1), 1) : gemm2_block_k(i + gemm2_k0(0), 0);
                        bulk_load(sb + gstage_off(s), hb + (size_t)blk * BLK, BLK, sb + GFULL + 8 * s);
                        TS(40 + i);
                    }
                }
            }
        }
    } else {
        asm volatile("setmaxnreg.inc.sync.aligned.u32 232;");
        const int wg = warp >> 2, w = warp & 3;
        const uint32_t stg = sb + OFF_STG;
        const uint32_t st_row = (uint32_t)(16 * w + (lane & 15)) * 128;
        const uint32_t st_sw = lane & 7, st_hi = lane >> 4;
        const int grow = 16 * w + (lane >> 2);

        if (wg == 1) {
            const int row0 = 128 * rb + 16 * j + 4 * w;
            uint4 v[4][2];
#pragma unroll
            for (int r = 0; r < 4; r++) {
                v[r][0] = *reinterpret_cast<const uint4*>(p.xp + (size_t)(row0 + r) * DM + 8 * lane);
                v[r][1] = *reinterpret_cast<const uint4*>(p.xp + (size_t)(row0 + r) * DM + 256 + 8 * lane);
            }
            const uint4 wa = *reinterpret_cast<const uint4*>(p.gate_w + 8 * lane);
            const uint4 wb = *reinterpret_cast<const uint4*>(p.gate_w + 256 + 8 * lane);
            const uint32_t ww[8] = {wa.x, wa.y, wa.z, wa.w, wb.x, wb.y, wb.z, wb.w};
            float mine = 0.f;
#pragma unroll
            for (int r = 0; r < 4; r++) {
                const uint32_t vv[8] = {v[r][0].x, v[r][0].y, v[r][0].z, v[r][0].w, v[r][1].x, v[r][1].y, v[r][1].z, v[r][1].w};
                float s0 = 0.f, s1 = 0.f;
#pragma unroll
                for (int i = 0; i < 8; i++) {
                    s0 = fmaf(__uint_as_float(vv[i] << 16), __uint_as_float(ww[i] << 16), s0);
                    s1 = fmaf(__uint_as_float(vv[i] & 0xffff0000u), __uint_as_float(ww[i] & 0xffff0000u), s1);
                }
                float s = s0 + s1;
#pragma unroll
                for (int o = 16; o > 0; o >>= 1) s += __shfl_xor_sync(0xffffffffu, s, o);
                if (lane == r) mine = s;
            }
            mbar_wait(sb + EREADY, 0);
            uint32_t epoch;
            asm volatile("ld.shared.u32 %0, [%1];" : "=r"(epoch) : "r"(sb + OFF_EPOCH) : "memory");
            if (lane < 4) {
                const float g = ex2(-1.4426950408889634f * mine);
                const unsigned long long e = ((unsigned long long)(epoch + 1) << 32) | __float_as_uint(g);
                asm volatile("st.relaxed.gpu.global.u64 [%0], %1;" ::"l"(g_gate + row0 + lane), "l"(e) : "memory");
            }
            if (threadIdx.x == 128) TS(35);
        }

        for (int slot = wg; slot < 5; slot += 2) {
            float acc[2][64];
            if (slot > 0) bar_sync(wg == 0 ? BAR_ORDER0 : BAR_ORDER1, 256);
            if ((threadIdx.x & 127) == 0) TS(2 + 4 * slot);
            const uint64_t da0 = desc_a(sb + OFF_X), db0 = desc_b(sb + OFF_B);
            if (slot == 0) mbar_wait(sb + XFULL, 0);
            mbar_wait(sb + BFULL, 0);
            if ((threadIdx.x & 127) == 0) TS(3 + 4 * slot);
#pragma unroll
            for (int kb = 0; kb < 8; kb++) {
                const uint64_t da = da0 + kb * 1024, db = db0 + (kb & 3) * 1024;
                if (kb == 7) bar_arrive(wg == 0 ? BAR_ORDER1 : BAR_ORDER0, 256);
                wgmma_fence();
                if (kb == 0) { wgmma_n128_first(acc[0], da, db); wgmma_n128_first(acc[1], da + 512, db); }
                else { wgmma_n128(acc[0], da, db); wgmma_n128(acc[1], da + 512, db); }
                wgmma_n128(acc[0], da + 2, db + 128);
                wgmma_n128(acc[1], da + 514, db + 128);
                wgmma_commit();
                if (kb > 0) {
                    wgmma_wait<1>();
                    if (lane == 0) {
                        mbar_arrive(sb + BEMPTY + 8 * ((kb - 1) & 3));
                        if (slot == 4) {
                            if (kb == 2) mbar_arrive(sb + GEMPTY + 0);
                            if (kb == 4) mbar_arrive(sb + GEMPTY + 8);
                            if (kb == 6) { mbar_arrive(sb + GEMPTY + 16); mbar_arrive(sb + GEMPTY + 24); }
                        }
                    }
                }
                wgmma_fence();
                wgmma_n128(acc[0], da + 4, db + 256);
                wgmma_n128(acc[1], da + 516, db + 256);
                wgmma_commit();
                if (kb < 7) {
                    if (slot == 0) mbar_wait(sb + XFULL + 8 * (kb + 1), 0);
                    mbar_wait(sb + BFULL + 8 * ((kb + 1) & 3), ((kb + 1) >> 2) & 1);
                }
                wgmma_fence();
                wgmma_n128(acc[0], da + 6, db + 384);
                wgmma_n128(acc[1], da + 518, db + 384);
                wgmma_commit();
            }
            wgmma_wait<0>();
            fence_regs(acc[0]); fence_regs(acc[1]);
            if (lane == 0) {
                mbar_arrive(sb + BEMPTY + 24);
                if (slot == 4) { mbar_arrive(sb + GEMPTY + 32); mbar_arrive(sb + GEMPTY + 40); }
                if (slot == 3) for (int i = 0; i < 6; i++) mbar_arrive(sb + GEMPTY + 8 * i);
            }
            if ((threadIdx.x & 127) == 0) TS(4 + 4 * slot);

            if (slot == 0) {
#pragma unroll
                for (int b = 0; b < 2; b++) {
#pragma unroll
                    for (int jp = 0; jp < 4; jp++) {
                        const uint32_t a = stg + b * 8192 + st_row + (((2 * jp + st_hi) ^ st_sw) << 4);
                        const float* k = &acc[b][8 * jp];
                        stsm_x4(a, phi2(k[0], k[1]), phi2(k[2], k[3]), phi2(k[4], k[5]), phi2(k[6], k[7]));
                        const float* v = &acc[b][32 + 8 * jp];
                        stsm_x4(a + BLK, pack2(v[0], v[1]), pack2(v[2], v[3]), pack2(v[4], v[5]), pack2(v[6], v[7]));
                    }
                }
                asm volatile("fence.proxy.async.shared::cta;" ::: "memory");
                bar_sync(BAR_WG0, 128);
                float d[36];
#pragma unroll
                for (int i = 0; i < 36; i++) d[i] = 0.f;
                wgmma_fence();
#pragma unroll
                for (int t = 0; t < 8; t++) {
                    const uint32_t vb = stg + BLK + t * 2048;
                    const uint64_t db = (uint64_t)(((vb & 0x3FFFF) >> 4) | (((OFF_ONES - OFF_STG - BLK - t * 2048) >> 4) << 16)) | ((uint64_t)(64u | (1u << 30)) << 32);
                    wgmma_n72_tt(d, desc_b(stg + t * 2048), db);
                }
                wgmma_commit();
                mbar_wait(sb + EREADY, 0);
                uint32_t epoch;
                asm volatile("ld.shared.u32 %0, [%1];" : "=r"(epoch) : "r"(sb + OFF_EPOCH) : "memory");
                float* dst = &g_kvacc[epoch & 1][4 * j + w][0];
                wgmma_wait<0>();
                fence_regs(d);
                float c[8];
#pragma unroll
                for (int i = 0; i < 8; i++) c[i] = w == 0 ? d[i] : w == 1 ? d[8 + i] : w == 2 ? d[16 + i] : d[24 + i];
                red_add_v4(dst + lane * 8, c[0], c[1], c[2], c[3]);
                red_add_v4(dst + lane * 8 + 4, c[4], c[5], c[6], c[7]);
                if ((lane & 3) < 2)
                    asm volatile("red.relaxed.gpu.global.add.f32 [%0], %1;" ::"l"(dst + 256 + (lane >> 2) + 8 * (lane & 1)), "f"((lane & 1) ? d[34] : d[32]) : "memory");
            } else if (slot == 2 && rank == 0) {
                uint32_t a[2][2][4];
#define PACK_Q(buf, h)                                                                                        \
    _Pragma("unroll") for (int b = 0; b < 2; b++) {                                                           \
        const float* q = &acc[b][8 * (h)];                                                                    \
        _Pragma("unroll") for (int i = 0; i < 4; i++) a[buf][b][i] = phi2(q[2 * i], q[2 * i + 1]); \
    }
                PACK_Q(0, 0)
                mbar_wait(sb + GREADY, 0);
                mbar_wait(sb + KVREADY, 0);
                mbar_wait(sb + STGFREE, 1);
                float g[4], ge[4];
#pragma unroll
                for (int i = 0; i < 4; i++) {
                    g[i] = 1.f + lds_f32(sb + OFF_G + 4 * (64 * (i >> 1) + grow + 8 * (i & 1)));
                    ge[i] = g[i] * 1e-6f;
                }
                const uint64_t dkv = (uint64_t)((((stg + BLK) & 0x3FFFF) >> 4) | (8u << 16)) | ((uint64_t)16u << 32);
                uint32_t held[3][2][4];
#pragma unroll
                for (int h = 0; h < 8; h++) {
                    float d[2][12];
                    wgmma_fence();
                    wgmma_n24_rs(d[0], a[h & 1][0], dkv + 48 * h);
                    wgmma_n24_rs(d[1], a[h & 1][1], dkv + 48 * h);
                    wgmma_commit();
                    if (h < 7) { PACK_Q((h + 1) & 1, h + 1) }
                    wgmma_wait<0>();
                    if (h == 7) bar_sync(BAR_WG0, 128);
#pragma unroll
                    for (int b = 0; b < 2; b++) {
                        fence_regs(d[b]);
                        const float r0 = rcp(fmaf(d[b][8], g[2 * b], ge[2 * b])), r1 = rcp(fmaf(d[b][10], g[2 * b + 1], ge[2 * b + 1]));
                        const uint32_t o0 = pack2(d[b][0] * r0, d[b][1] * r0), o1 = pack2(d[b][2] * r1, d[b][3] * r1);
                        const uint32_t o2 = pack2(d[b][4] * r0, d[b][5] * r0), o3 = pack2(d[b][6] * r1, d[b][7] * r1);
                        const uint32_t dst = stg + (h >> 2) * BLK + b * 8192 + st_row;
                        if (h >= 4 && h < 7) { held[h - 4][b][0] = o0; held[h - 4][b][1] = o1; held[h - 4][b][2] = o2; held[h - 4][b][3] = o3; }
                        else stsm_x4(dst + (((2 * (h & 3) + st_hi) ^ st_sw) << 4), o0, o1, o2, o3);
                        if (h == 7) {
#pragma unroll
                            for (int k = 0; k < 3; k++)
                                stsm_x4(dst + (((2 * k + st_hi) ^ st_sw) << 4), held[k][b][0], held[k][b][1], held[k][b][2], held[k][b][3]);
                        }
                    }
                }
#undef PACK_Q
                asm volatile("fence.proxy.async.shared::cta;" ::: "memory");
            } else {
                mbar_wait(sb + GREADY, 0);
                mbar_wait(sb + STGFREE, (slot - 1) & 1);
#pragma unroll
                for (int b = 0; b < 2; b++) {
                    const float f0 = 1.f - rcp(1.f + lds_f32(sb + OFF_G + 4 * (64 * b + grow)));
                    const float f1 = 1.f - rcp(1.f + lds_f32(sb + OFF_G + 4 * (64 * b + grow + 8)));
                    const uint32_t s0 = pack2(f0, f0), s1 = pack2(f1, f1);
#pragma unroll
                    for (int jp = 0; jp < 4; jp++) {
                        const float* g = &acc[b][8 * jp];
                        const float* u = &acc[b][32 + 8 * jp];
                        const uint32_t a = stg + b * 8192 + st_row + (((2 * jp + st_hi) ^ st_sw) << 4);
                        stsm_x4(a, hmul2(pack2(g[0] * u[0], g[1] * u[1]), s0), hmul2(pack2(g[2] * u[2], g[3] * u[3]), s1),
                                hmul2(pack2(g[4] * u[4], g[5] * u[5]), s0), hmul2(pack2(g[6] * u[6], g[7] * u[7]), s1));
                    }
                }
                asm volatile("fence.proxy.async.shared::cta;" ::: "memory");
            }
            bar_arrive(BAR_STORE, 160);
            if ((threadIdx.x & 127) == 0) TS(5 + 4 * slot);
        }

        float acc[64];
#pragma unroll
        for (int i = 0; i < 64; i++) acc[i] = 0.f;
        asm volatile("barrier.cluster.wait.aligned;" ::: "memory");
        if (wg == 1) bar_sync(BAR_ORDER1, 256);
        const int half = wg == 0 ? rank : rank ^ 1;
        if ((threadIdx.x & 127) == 0) TS(22 + 4 * wg);
        const int nblk = gemm2_n(rank);
        {
            uint64_t da = desc_a(sb + half * 8192), db = desc_b(sb + BLK);
            uint32_t s = 0, ph = 0;
            mbar_wait(sb + GFULL, 0);
#pragma unroll 1
            for (int i = 0; i < nblk; i++) {
                if (wg == 0 && i == nblk - TAIL_LEAD) bar_sync(BAR_TAIL, 256);
                if (wg == 1 && i == nblk - 1) bar_arrive(BAR_TAIL, 256);
                wgmma_fence();
                wgmma_n128(acc, da, db);
                wgmma_n128(acc, da + 2, db + 128);
                wgmma_commit();
                wgmma_wait<1>();
                if (lane == 0 && i > 0) mbar_arrive(sb + GEMPTY + 8 * (s == 0 ? 5 : s - 1));
                wgmma_fence();
                wgmma_n128(acc, da + 4, db + 256);
                wgmma_commit();
                const int64_t step = s == 2 ? 4096 : s == 3 ? -2048 : s == 4 ? 4096 : s == 5 ? -10240 : 2048;
                if (++s == 6) { s = 0; ph ^= 1; }
                if (i + 1 < nblk) mbar_wait(sb + GFULL + 8 * s, ph);
                wgmma_fence();
                wgmma_n128(acc, da + 6, db + 384);
                wgmma_commit();
                da += step; db += step;
            }
        }
        const uint32_t rx = stg + w * 8192 + lane * 16;
        if (wg == 1) {
            mbar_wait(sb + TXOK, 0);
            const uint32_t dst = mapa(rx, rank ^ 1), bar = mapa(sb + RXFULL + 8 * w, rank ^ 1);
            wgmma_wait<0>();
            fence_regs(acc);
            if ((threadIdx.x & 127) == 0) TS(27);
#pragma unroll
            for (int i = 0; i < 16; i++)
                asm volatile("st.async.weak.shared::cluster.mbarrier::complete_tx::bytes.v4.f32 [%0], {%1,%2,%3,%4}, [%5];"
                             ::"r"(dst + i * 512), "f"(acc[4 * i]), "f"(acc[4 * i + 1]), "f"(acc[4 * i + 2]), "f"(acc[4 * i + 3]), "r"(bar) : "memory");
            if ((threadIdx.x & 127) == 0) TS(28);
        } else {
            mbar_wait(sb + RXFULL + 8 * w, 0);
            if ((threadIdx.x & 127) == 0) TS(24);
            float4 v[16];
#pragma unroll
            for (int i = 0; i < 16; i++)
                asm volatile("ld.shared.v4.f32 {%0,%1,%2,%3}, [%4];" : "=f"(v[i].x), "=f"(v[i].y), "=f"(v[i].z), "=f"(v[i].w) : "r"(rx + i * 512) : "memory");
            wgmma_wait<0>();
            fence_regs(acc);
            if ((threadIdx.x & 127) == 0) TS(23);
#pragma unroll
            for (int i = 0; i < 16; i++) {
                acc[4 * i] += v[i].x; acc[4 * i + 1] += v[i].y; acc[4 * i + 2] += v[i].z; acc[4 * i + 3] += v[i].w;
            }
            __syncwarp();
            const uint32_t ob = stg + w * 8192 + (uint32_t)(lane & 15) * 128;
#pragma unroll
            for (int jp = 0; jp < 8; jp++) {
                const float* o = &acc[8 * jp];
                stsm_x4(ob + (jp >> 2) * 2048 + (((2 * (jp & 3) + st_hi) ^ st_sw) << 4),
                        pack2(o[0], o[1]), pack2(o[2], o[3]), pack2(o[4], o[5]), pack2(o[6], o[7]));
            }
            asm volatile("fence.proxy.async.shared::cta;" ::: "memory");
            __syncwarp();
            if (elect_one()) {
                tma_store_3d(&p.out, stg + w * 8192, 0, 128 * rb + 64 * rank + 16 * w, 2 * ct);
                asm volatile("cp.async.bulk.commit_group;" ::: "memory");
                asm volatile("cp.async.bulk.wait_group.read 0;" ::: "memory");
                if (w == 0) { TS(25); TSG(63); }
            }
        }
    }
}

typedef CUresult (*EncodeFn)(CUtensorMap*, CUtensorMapDataType, cuuint32_t, void*, const cuuint64_t*, const cuuint64_t*,
                             const cuuint32_t*, const cuuint32_t*, CUtensorMapInterleave, CUtensorMapSwizzle,
                             CUtensorMapL2promotion, CUtensorMapFloatOOBfill);

void make_2d(EncodeFn enc, CUtensorMap* m, const void* ptr, uint64_t rows, uint64_t cols, uint32_t brows) {
    cuuint64_t dims[2] = {cols, rows};
    cuuint64_t strides[1] = {cols * 2};
    cuuint32_t box[2] = {64, brows};
    cuuint32_t es[2] = {1, 1};
    CUresult r = enc(m, CU_TENSOR_MAP_DATA_TYPE_BFLOAT16, 2, const_cast<void*>(ptr), dims, strides, box, es,
                     CU_TENSOR_MAP_INTERLEAVE_NONE, CU_TENSOR_MAP_SWIZZLE_128B, CU_TENSOR_MAP_L2_PROMOTION_L2_128B,
                     CU_TENSOR_MAP_FLOAT_OOB_FILL_NONE);
    if (r != CUDA_SUCCESS) fprintf(stderr, "tensor map 2d failed: %d\n", (int)r);
}
void make_3d(EncodeFn enc, CUtensorMap* m, const void* ptr, uint64_t rows, uint64_t cols, uint32_t brows) {
    cuuint64_t dims[3] = {64, rows, cols / 64};
    cuuint64_t strides[2] = {cols * 2, 128};
    cuuint32_t box[3] = {64, brows, 2};
    cuuint32_t es[3] = {1, 1, 1};
    CUresult r = enc(m, CU_TENSOR_MAP_DATA_TYPE_BFLOAT16, 3, const_cast<void*>(ptr), dims, strides, box, es,
                     CU_TENSOR_MAP_INTERLEAVE_NONE, CU_TENSOR_MAP_SWIZZLE_128B, CU_TENSOR_MAP_L2_PROMOTION_L2_128B,
                     CU_TENSOR_MAP_FLOAT_OOB_FILL_NONE);
    if (r != CUDA_SUCCESS) fprintf(stderr, "tensor map 3d failed: %d\n", (int)r);
}

}

extern "C" void kernel_launch(void* const* d_in, const int* in_sizes, int n_in, void* d_out, int out_size) {
    (void)in_sizes; (void)n_in; (void)out_size;
    static EncodeFn enc = nullptr;
    if (!enc) {
        void* fn = nullptr;
        cudaDriverEntryPointQueryResult qr;
        cudaGetDriverEntryPoint("cuTensorMapEncodeTiled", &fn, cudaEnableDefault, &qr);
        enc = (EncodeFn)fn;
        cudaFuncSetAttribute(fused_kernel, cudaFuncAttributeMaxDynamicSharedMemorySize, SMEM_BYTES);
    }
    Params p;
    make_2d(enc, &p.x, d_in[0], SEQ, DM, 128);
    make_2d(enc, &p.qkv, d_in[1], DM, 3 * DM, 64);
    make_3d(enc, &p.wo, d_in[2], DM, DM, 64);
    make_2d(enc, &p.wg, d_in[4], DM, FF, 64);
    make_2d(enc, &p.wu, d_in[5], DM, FF, 64);
    make_3d(enc, &p.wd, d_in[6], FF, DM, 64);
    make_3d(enc, &p.out, d_out, SEQ, DM, 16);
    p.gate_w = (const __nv_bfloat16*)d_in[7];
    p.xp = (const __nv_bfloat16*)d_in[0];
    fused_kernel<<<128, 384, SMEM_BYTES, cudaStreamPerThread>>>(p);
}
```

```cpp
#include <cuda_runtime.h>
#include <cuda_bf16.h>
#include <cuda.h>
#include <stdint.h>
#include <stdio.h>

#define L2PROMO CU_TENSOR_MAP_L2_PROMOTION_L2_256B
#define PF0 0
#define PF1 2
#define PF2 7
#define EARLYPF 1
#define STI 1
#define PRE 1
#define PACE 3
namespace {

constexpr int SEQ = 2048, DM = 512, FF = 1792;
constexpr int NKB2 = 36;
constexpr uint32_t BLK = 16384;

constexpr uint32_t OFF_X = 0;
constexpr int NSLOT = 5;
constexpr uint32_t OFF_B = 131072;
constexpr uint32_t OFF_RX = 196608;
constexpr uint32_t OFF_STG = 212992;
constexpr uint32_t OFF_ONES = 229376;
constexpr uint32_t OFF_G = 231424;
constexpr uint32_t OFF_BAR = 231936;
constexpr uint32_t XFULL = OFF_BAR, BFULL = XFULL + 64, BEMPTY = BFULL + 64, GFULL = BEMPTY + 64,
                   GEMPTY = GFULL + 48, GREADY = GEMPTY + 48, EREADY = GREADY + 8,
                   STGFREE = EREADY + 8, QFREE = STGFREE + 8, TXOK = QFREE + 8, RXFULL = TXOK + 8, OFF_EPOCH = RXFULL + 32;
constexpr uint32_t SMEM_BYTES = OFF_EPOCH + 16;

constexpr int BAR_ORDER0 = 1, BAR_ORDER1 = 2, BAR_WG0 = 3, BAR_WG1 = 4, BAR_STORE = 5;
#define TAIL_LEAD 5

__device__ __align__(1024) uint8_t g_hbuf[16 * NKB2 * BLK];
__device__ __align__(128) uint32_t g_flags[16 * 64];
__device__ uint32_t g_kvcnt[8 * 32];
__device__ __align__(128) float g_kvacc[2][32][272];
__device__ unsigned long long g_gate[SEQ];

#define TS(i) do {} while (0)
#define TSG(i) do {} while (0)
#define TSN(i) do {} while (0)
#define TW_DECL() do {} while (0)
#define TW_BEGIN() do {} while (0)
#define TW_END(acc) do {} while (0)
#define TSV(i, v) do {} while (0)

constexpr uint32_t SPIN_LIMIT = 1u << 24;

__device__ __forceinline__ uint32_t smem_u32(const void* p) { return (uint32_t)__cvta_generic_to_shared(p); }
__device__ __forceinline__ void mbar_init(uint32_t bar, uint32_t cnt) {
    asm volatile("mbarrier.init.shared::cta.b64 [%0], %1;" ::"r"(bar), "r"(cnt) : "memory");
}
__device__ __forceinline__ void mbar_expect_tx(uint32_t bar, uint32_t bytes) {
    asm volatile("mbarrier.arrive.expect_tx.shared::cta.b64 _, [%0], %1;" ::"r"(bar), "r"(bytes) : "memory");
}
__device__ __forceinline__ void mbar_arrive(uint32_t bar) {
    asm volatile("mbarrier.arrive.shared::cta.b64 _, [%0];" ::"r"(bar) : "memory");
}
__device__ __forceinline__ void mbar_arrive2(uint32_t bar) {
    asm volatile("mbarrier.arrive.shared::cta.b64 _, [%0], 2;" ::"r"(bar) : "memory");
}
__device__ __forceinline__ uint32_t mapa(uint32_t addr, uint32_t cta) {
    uint32_t r;
    asm volatile("mapa.shared::cluster.u32 %0, %1, %2;" : "=r"(r) : "r"(addr), "r"(cta));
    return r;
}
__device__ __forceinline__ void mbar_arrive_remote(uint32_t remote_bar) {
    asm volatile("mbarrier.arrive.shared::cluster.b64 _, [%0];" ::"r"(remote_bar) : "memory");
}
__device__ __forceinline__ void mbar_wait(uint32_t bar, uint32_t parity) {
    asm volatile("{\n.reg .pred p;\n.reg .u32 n;\nmov.u32 n, 0;\nWAIT_LOOP:\n"
                 "mbarrier.try_wait.parity.shared::cta.b64 p, [%0], %1;\n@p bra WAIT_DONE;\n"
                 "add.u32 n, n, 1;\nsetp.lt.u32 p, n, 0x400000;\n@p bra WAIT_LOOP;\ntrap;\nWAIT_DONE:\n}" ::"r"(bar), "r"(parity) : "memory");
}
__device__ __forceinline__ void bar_sync(int id, int n) { asm volatile("bar.sync %0, %1;" ::"r"(id), "r"(n) : "memory"); }
__device__ __forceinline__ void bar_arrive(int id, int n) { asm volatile("bar.arrive %0, %1;" ::"r"(id), "r"(n) : "memory"); }

__device__ __forceinline__ void tma_load_2d(uint32_t dst, const CUtensorMap* tm, int c0, int c1, uint32_t bar) {
    asm volatile("cp.async.bulk.tensor.2d.shared::cluster.global.mbarrier::complete_tx::bytes [%0], [%1, {%3, %4}], [%2];"
                 ::"r"(dst), "l"(tm), "r"(bar), "r"(c0), "r"(c1) : "memory");
}
__device__ __forceinline__ void tma_load_3d(uint32_t dst, const CUtensorMap* tm, int c0, int c1, int c2, uint32_t bar) {
    asm volatile("cp.async.bulk.tensor.3d.shared::cluster.global.mbarrier::complete_tx::bytes [%0], [%1, {%3, %4, %5}], [%2];"
                 ::"r"(dst), "l"(tm), "r"(bar), "r"(c0), "r"(c1), "r"(c2) : "memory");
}
__device__ __forceinline__ void tma_prefetch_2d(const CUtensorMap* tm, int c0, int c1) {
    asm volatile("cp.async.bulk.prefetch.tensor.2d.L2.global.tile [%0, {%1, %2}];" ::"l"(tm), "r"(c0), "r"(c1) : "memory");
}
__device__ __forceinline__ void tma_prefetch_3d(const CUtensorMap* tm, int c0, int c1, int c2) {
    asm volatile("cp.async.bulk.prefetch.tensor.3d.L2.global.tile [%0, {%1, %2, %3}];" ::"l"(tm), "r"(c0), "r"(c1), "r"(c2) : "memory");
}
__device__ __forceinline__ void tma_store_3d(const CUtensorMap* tm, uint32_t src, int c0, int c1, int c2) {
    asm volatile("cp.async.bulk.tensor.3d.global.shared::cta.bulk_group [%0, {%2, %3, %4}], [%1];"
                 ::"l"(tm), "r"(src), "r"(c0), "r"(c1), "r"(c2) : "memory");
}
__device__ __forceinline__ void bulk_load(uint32_t dst, const void* src, uint32_t bytes, uint32_t bar) {
    asm volatile("cp.async.bulk.shared::cluster.global.mbarrier::complete_tx::bytes [%0], [%1], %2, [%3];"
                 ::"r"(dst), "l"(src), "r"(bytes), "r"(bar) : "memory");
}
__device__ __forceinline__ void bulk_store(void* dst, uint32_t src, uint32_t bytes) {
    asm volatile("cp.async.bulk.global.shared::cta.bulk_group [%0], [%1], %2;" ::"l"(dst), "r"(src), "r"(bytes) : "memory");
}
__device__ __forceinline__ void prefetch_tmap(const CUtensorMap* tm) {
    asm volatile("prefetch.tensormap [%0];" ::"l"(tm) : "memory");
}
__device__ __forceinline__ uint32_t ld_acquire(const uint32_t* p) {
    uint32_t v;
    asm volatile("ld.acquire.gpu.global.u32 %0, [%1];" : "=r"(v) : "l"(p) : "memory");
    return v;
}
__device__ __forceinline__ uint32_t ld_relaxed(const uint32_t* p) {
    uint32_t v;
    asm volatile("ld.relaxed.gpu.global.u32 %0, [%1];" : "=r"(v) : "l"(p) : "memory");
    return v;
}
__device__ __forceinline__ void wait_count(const uint32_t* p, uint32_t target) {
    asm volatile("{\n.reg .pred p;\n.reg .u32 n, v;\nmov.u32 n, 0;\nCNT_LOOP:\n"
                 "ld.acquire.gpu.global.u32 v, [%0];\nsub.u32 v, v, %1;\nsetp.ge.s32 p, v, 0;\n@p bra CNT_DONE;\n"
                 "add.u32 n, n, 1;\nsetp.lt.u32 p, n, 0x400000;\n@p bra CNT_LOOP;\ntrap;\nCNT_DONE:\n}" ::"l"(p), "r"(target) : "memory");
}
__device__ __forceinline__ void st_relaxed(uint32_t* p, uint32_t v) {
    asm volatile("st.relaxed.gpu.global.u32 [%0], %1;" ::"l"(p), "r"(v) : "memory");
}
__device__ __forceinline__ void red_add_v4(float* p, float a, float b, float c, float d) {
    asm volatile("red.relaxed.gpu.global.add.v4.f32 [%0], {%1, %2, %3, %4};" ::"l"(p), "f"(a), "f"(b), "f"(c), "f"(d) : "memory");
}
__device__ __forceinline__ float4 ld_cg4(const float* p) {
    float4 v;
    asm volatile("ld.relaxed.gpu.global.v4.f32 {%0, %1, %2, %3}, [%4];" : "=f"(v.x), "=f"(v.y), "=f"(v.z), "=f"(v.w) : "l"(p) : "memory");
    return v;
}
__device__ __forceinline__ void wgmma_fence() { asm volatile("wgmma.fence.sync.aligned;" ::: "memory"); }
__device__ __forceinline__ void wgmma_commit() { asm volatile("wgmma.commit_group.sync.aligned;" ::: "memory"); }
template <int N> __device__ __forceinline__ void wgmma_wait() { asm volatile("wgmma.wait_group.sync.aligned %0;" ::"n"(N) : "memory"); }

__device__ __forceinline__ uint64_t desc_a(uint32_t addr) {
    return (uint64_t)(((addr & 0x3FFFF) >> 4) | (1u << 16)) | ((uint64_t)(64u | (1u << 30)) << 32);
}
__device__ __forceinline__ uint64_t desc_b(uint32_t addr, uint32_t lbo = 8192) {
    return (uint64_t)(((addr & 0x3FFFF) >> 4) | ((lbo >> 4) << 16)) | ((uint64_t)(64u | (1u << 30)) << 32);
}
#define ACC8(a, o) "+f"(a[o + 0]), "+f"(a[o + 1]), "+f"(a[o + 2]), "+f"(a[o + 3]), "+f"(a[o + 4]), "+f"(a[o + 5]), "+f"(a[o + 6]), "+f"(a[o + 7])
__device__ __forceinline__ void wgmma_n128(float (&d)[64], uint64_t da, uint64_t db) {
    asm volatile("wgmma.mma_async.sync.aligned.m64n128k16.f32.bf16.bf16 "
                 "{%0,%1,%2,%3,%4,%5,%6,%7,%8,%9,%10,%11,%12,%13,%14,%15,%16,%17,%18,%19,%20,%21,%22,%23,%24,%25,%26,%27,%28,%29,%30,%31,"
                 "%32,%33,%34,%35,%36,%37,%38,%39,%40,%41,%42,%43,%44,%45,%46,%47,%48,%49,%50,%51,%52,%53,%54,%55,%56,%57,%58,%59,%60,%61,%62,%63},"
                 " %64, %65, 1, 1, 1, 0, 1;"
                 : ACC8(d, 0), ACC8(d, 8), ACC8(d, 16), ACC8(d, 24), ACC8(d, 32), ACC8(d, 40), ACC8(d, 48), ACC8(d, 56)
                 : "l"(da), "l"(db));
}
#define OUT8(a, o) "=f"(a[o + 0]), "=f"(a[o + 1]), "=f"(a[o + 2]), "=f"(a[o + 3]), "=f"(a[o + 4]), "=f"(a[o + 5]), "=f"(a[o + 6]), "=f"(a[o + 7])
__device__ __forceinline__ void wgmma_n128_first(float (&d)[64], uint64_t da, uint64_t db) {
    asm volatile("wgmma.mma_async.sync.aligned.m64n128k16.f32.bf16.bf16 "
                 "{%0,%1,%2,%3,%4,%5,%6,%7,%8,%9,%10,%11,%12,%13,%14,%15,%16,%17,%18,%19,%20,%21,%22,%23,%24,%25,%26,%27,%28,%29,%30,%31,"
                 "%32,%33,%34,%35,%36,%37,%38,%39,%40,%41,%42,%43,%44,%45,%46,%47,%48,%49,%50,%51,%52,%53,%54,%55,%56,%57,%58,%59,%60,%61,%62,%63},"
                 " %64, %65, 0, 1, 1, 0, 1;"
                 : OUT8(d, 0), OUT8(d, 8), OUT8(d, 16), OUT8(d, 24), OUT8(d, 32), OUT8(d, 40), OUT8(d, 48), OUT8(d, 56)
                 : "l"(da), "l"(db));
}
__device__ __forceinline__ void wgmma_n128_restart(float (&d)[64], uint64_t da, uint64_t db) {
    asm volatile("wgmma.mma_async.sync.aligned.m64n128k16.f32.bf16.bf16 "
                 "{%0,%1,%2,%3,%4,%5,%6,%7,%8,%9,%10,%11,%12,%13,%14,%15,%16,%17,%18,%19,%20,%21,%22,%23,%24,%25,%26,%27,%28,%29,%30,%31,"
                 "%32,%33,%34,%35,%36,%37,%38,%39,%40,%41,%42,%43,%44,%45,%46,%47,%48,%49,%50,%51,%52,%53,%54,%55,%56,%57,%58,%59,%60,%61,%62,%63},"
                 " %64, %65, 0, 1, 1, 0, 1;"
                 : ACC8(d, 0), ACC8(d, 8), ACC8(d, 16), ACC8(d, 24), ACC8(d, 32), ACC8(d, 40), ACC8(d, 48), ACC8(d, 56)
                 : "l"(da), "l"(db));
}
template <bool ACC>
__device__ __forceinline__ void wgmma_n72_tt(float (&d)[36], uint64_t da, uint64_t db) {
    if (ACC)
        asm volatile("wgmma.mma_async.sync.aligned.m64n72k16.f32.bf16.bf16 "
                     "{%0,%1,%2,%3,%4,%5,%6,%7,%8,%9,%10,%11,%12,%13,%14,%15,%16,%17,%18,%19,%20,%21,%22,%23,%24,%25,%26,%27,%28,%29,%30,%31,"
                     "%32,%33,%34,%35}, %36, %37, 1, 1, 1, 1, 1;"
                     : ACC8(d, 0), ACC8(d, 8), ACC8(d, 16), ACC8(d, 24), "+f"(d[32]), "+f"(d[33]), "+f"(d[34]), "+f"(d[35])
                     : "l"(da), "l"(db));
    else
        asm volatile("wgmma.mma_async.sync.aligned.m64n72k16.f32.bf16.bf16 "
                     "{%0,%1,%2,%3,%4,%5,%6,%7,%8,%9,%10,%11,%12,%13,%14,%15,%16,%17,%18,%19,%20,%21,%22,%23,%24,%25,%26,%27,%28,%29,%30,%31,"
                     "%32,%33,%34,%35}, %36, %37, 0, 1, 1, 1, 1;"
                     : OUT8(d, 0), OUT8(d, 8), OUT8(d, 16), OUT8(d, 24), "=f"(d[32]), "=f"(d[33]), "=f"(d[34]), "=f"(d[35])
                     : "l"(da), "l"(db));
}
__device__ __forceinline__ void wgmma_n24_rs(float (&d)[12], const uint32_t (&a)[4], uint64_t db) {
    asm volatile("wgmma.mma_async.sync.aligned.m64n24k16.f32.bf16.bf16 "
                 "{%0,%1,%2,%3,%4,%5,%6,%7,%8,%9,%10,%11}, {%12,%13,%14,%15}, %16, 0, 1, 1, 1;"
                 : "=f"(d[0]), "=f"(d[1]), "=f"(d[2]), "=f"(d[3]), "=f"(d[4]), "=f"(d[5]), "=f"(d[6]), "=f"(d[7]),
                   "=f"(d[8]), "=f"(d[9]), "=f"(d[10]), "=f"(d[11])
                 : "r"(a[0]), "r"(a[1]), "r"(a[2]), "r"(a[3]), "l"(db));
}
template <int N> __device__ __forceinline__ void fence_regs(float (&d)[N]) {
#pragma unroll
    for (int i = 0; i < N; i++) asm volatile("" : "+f"(d[i])::"memory");
}
__device__ __forceinline__ void stsm_x4(uint32_t addr, uint32_t r0, uint32_t r1, uint32_t r2, uint32_t r3) {
    asm volatile("stmatrix.sync.aligned.m8n8.x4.shared.b16 [%0], {%1,%2,%3,%4};" ::"r"(addr), "r"(r0), "r"(r1), "r"(r2), "r"(r3) : "memory");
}
__device__ __forceinline__ uint32_t pack2(float lo, float hi) {
    uint32_t r;
    asm("cvt.rn.bf16x2.f32 %0, %1, %2;" : "=r"(r) : "f"(hi), "f"(lo));
    return r;
}
__device__ __forceinline__ float lds_f32(uint32_t addr) {
    float v;
    asm volatile("ld.shared.f32 %0, [%1];" : "=f"(v) : "r"(addr) : "memory");
    return v;
}
__device__ __forceinline__ float ex2(float x) {
    float y;
    asm("ex2.approx.ftz.f32 %0, %1;" : "=f"(y) : "f"(x));
    return y;
}
__device__ __forceinline__ float rcp(float x) {
    float y;
    asm("rcp.approx.ftz.f32 %0, %1;" : "=f"(y) : "f"(x));
    return y;
}
__device__ __forceinline__ uint32_t hmul2(uint32_t a, uint32_t b) {
    uint32_t r;
    asm("mul.rn.bf16x2 %0, %1, %2;" : "=r"(r) : "r"(a), "r"(b));
    return r;
}
__device__ __forceinline__ uint32_t phi2(float t0, float t1, float log2e = 1.4426950408889634f) {
    uint32_t e = pack2(ex2(t0 * log2e), ex2(t1 * log2e));
    uint32_t t = pack2(t0, t1), r;
    asm("min.bf16x2 %0, %0, %1;" : "+r"(e) : "r"(0x3f803f80u));
    asm("max.bf16x2 %0, %0, %1;" : "+r"(t) : "r"(0x35863586u));
    asm("add.rn.bf16x2 %0, %1, %2;" : "=r"(r) : "r"(t), "r"(e));
    return r;
}
__device__ __forceinline__ float sched_fence(uint32_t opaque) {
    float l;
    asm volatile("{\n.reg .pred p;\nmov.f32 %0, 0f3FB8AA3B;\nsetp.ne.u32 p, %1, 1;\n@p bra SF_DONE;\nSF_LOOP:\n"
                 "ld.volatile.shared.f32 %0, [%1];\nsetp.eq.f32 p, %0, 0f00000000;\n@p bra SF_LOOP;\nSF_DONE:\n}" : "=f"(l) : "r"(opaque) : "memory");
    return l;
}
__device__ __forceinline__ bool elect_one() {
    uint32_t pred;
    asm volatile("{\n.reg .pred p;\nelect.sync _|p, 0xffffffff;\nselp.u32 %0, 1, 0, p;\n}" : "=r"(pred));
    return pred != 0;
}

struct Params {
    CUtensorMap x, qkv, wg, wu, wd, wo, out;
    const __nv_bfloat16* gate_w;
    const __nv_bfloat16* xp;
    const __nv_bfloat16* wqkv;
};

__device__ __forceinline__ int slot_block(int slot, int ct, int rank) {
    return slot == 3 ? 16 + ct : (slot == 4 ? 20 : 8 * (slot - 1)) + 2 * ct + rank;
}
__device__ __forceinline__ void slot_weights(const Params& p, int slot, int ct, int rank, const CUtensorMap*& m0,
                                             const CUtensorMap*& m1, int& c0, int& c1) {
    const int j = 2 * ct + rank;
    if (slot == 0) { m0 = m1 = &p.qkv; c0 = 512 + 64 * j; c1 = 1024 + 64 * j; }
    else if (slot == 3 && rank == 0) { m0 = m1 = &p.qkv; c0 = 128 * ct; c1 = c0 + 64; }
    else { m0 = &p.wg; m1 = &p.wu; c0 = c1 = 64 * slot_block(slot, ct, rank); }
}
#define EVEN 1
__device__ __forceinline__ constexpr int gemm2_n(int rank) { return EVEN ? 18 : 17 + 2 * rank; }
__device__ __forceinline__ constexpr int gemm2_block_(int i, int rank) {
    return rank == 0 ? (i < 8 ? 2 * i + 2 : i == 8 ? 17 : i < 11 ? 28 + 2 * (i - 9) : i < 15 ? 20 + 2 * (i - 11) : 29 + 2 * (i - 15))
                     : (i == 0 ? 0 : i < 9 ? 2 * i - 1 : i < 11 ? 9 + i : i < 13 ? 32 + 2 * (i - 11) : i < 17 ? 21 + 2 * (i - 13) : 33 + 2 * (i - 17));
}
__device__ __forceinline__ constexpr int gemm2_block(int i, int rank) {
    return !EVEN ? gemm2_block_(i, rank) : rank == 0 ? (i == 0 ? 0 : gemm2_block_(i - 1, 0)) : gemm2_block_(i + 1, 1);
}
__device__ __forceinline__ int block_flag_(int b) {
    if (b < 17) return b == 0 ? 32 : (b & 1) ? 32 + (b + 1) / 2 : b / 2 - 1;
    if (b < 20) return b == 17 ? 8 : 32 + b - 9;
    if (b < 28) return (b & 1) ? 32 + 13 + (b - 21) / 2 : 11 + (b - 20) / 2;
    if (b & 1) return b < 32 ? 15 + (b - 29) / 2 : 32 + 17 + (b - 33) / 2;
    return b < 32 ? 9 + (b - 28) / 2 : 32 + 11 + (b - 32) / 2;
}
__device__ __forceinline__ int block_flag(int b) {
    const int f = block_flag_(b);
    return !EVEN ? f : b == 0 ? 0 : f < 32 ? f + 1 : f - 1;
}
__device__ __forceinline__ constexpr uint32_t gstage_off(int s) { return (uint32_t)(s < 2 ? s : s == 2 ? 4 : s == 3 ? 2 : s == 4 ? 5 : 3) * 32768u; }

template <bool LAST>
__device__ __forceinline__ uint32_t tile_mainloop(float (&acc)[2][64], uint32_t sb, int slot, int wg, int lane) {
    TW_DECL();
    const uint64_t da0 = desc_a(sb + OFF_X), db0 = desc_b(sb + OFF_B);
    uint32_t s = (slot * 8) % NSLOT, ph = ((slot * 8) / NSLOT) & 1, prev = 0;
    if (!LAST && slot == 0) mbar_wait(sb + XFULL, 0);
    mbar_wait(sb + BFULL + 8 * s, ph);
    if ((threadIdx.x & 127) == 0) TS(3 + 4 * slot);
#pragma unroll
    for (int kb = 0; kb < 8; kb++) {
        const uint64_t da = da0 + kb * 1024, db = db0 + s * 1024;
        if (kb == 7 && !LAST) bar_arrive(wg == 0 ? BAR_ORDER1 : BAR_ORDER0, 256);
        wgmma_fence();
        if (kb == 0) {
            wgmma_n128_first(acc[0], da, db); wgmma_n128_first(acc[1], da + 512, db);
            wgmma_n128(acc[0], da + 2, db + 128); wgmma_n128(acc[1], da + 514, db + 128);
        } else if (kb < 7) {
            wgmma_n128(acc[0], da, db); wgmma_n128(acc[1], da + 512, db);
            wgmma_n128(acc[0], da + 2, db + 128); wgmma_n128(acc[1], da + 514, db + 128);
        } else {
            wgmma_n128(acc[0], da, db); wgmma_n128(acc[0], da + 2, db + 128);
            wgmma_n128(acc[0], da + 4, db + 256); wgmma_n128(acc[0], da + 6, db + 384);
        }
        wgmma_commit();
        if (kb > 0) {
            wgmma_wait<1>();
            if (lane == 0) {
                mbar_arrive(sb + BEMPTY + 8 * prev);
                if (LAST) {
                    if (kb == 2) mbar_arrive(sb + GEMPTY + 0);
                    if (kb >= 4) mbar_arrive(sb + GEMPTY + 8 * (kb - 3));
                }
            }
        }
        prev = s;
        if (++s == NSLOT) { s = 0; ph ^= 1; }
        if (kb < 7) {
            wgmma_fence();
            wgmma_n128(acc[0], da + 4, db + 256);
            wgmma_n128(acc[1], da + 516, db + 256);
            wgmma_commit();
            TW_BEGIN();
            if (!LAST && slot == 0) mbar_wait(sb + XFULL + 8 * (kb + 1), 0);
            mbar_wait(sb + BFULL + 8 * s, ph);
            TW_END(twait);
            wgmma_fence();
            wgmma_n128(acc[0], da + 6, db + 384);
            wgmma_n128(acc[1], da + 518, db + 384);
            wgmma_commit();
        } else {
            wgmma_fence();
            wgmma_n128(acc[1], da + 512, db); wgmma_n128(acc[1], da + 514, db + 128);
            wgmma_n128(acc[1], da + 516, db + 256); wgmma_n128(acc[1], da + 518, db + 384);
            wgmma_commit();
        }
    }
    if ((threadIdx.x & 127) == 0) TSV(2 + 4 * slot, twait);
    return prev;
}

__global__ void __cluster_dims__(2, 1, 1) __launch_bounds__(384, 1)
fused_kernel(const __grid_constant__ Params p) {
    extern __shared__ __align__(1024) uint8_t smem_raw[];
    const uint32_t sb = __shfl_sync(0xffffffffu, smem_u32(smem_raw), 0);
    const int warp = __shfl_sync(0xffffffffu, threadIdx.x >> 5, 0), lane = threadIdx.x & 31;
    const int rank = blockIdx.x & 1;
    int rb, ct;
    {
        const int c = blockIdx.x >> 1;
        if (c < 4) { rb = 15; ct = c; }
        else if (c < 36) { rb = (c - 4) & 7; ct = (c - 4) >> 3; }
        else { rb = 8 + (c - 36) % 7; ct = (c - 36) / 7; }
    }
    const int j = 2 * ct + rank;

    if (warp < EARLYPF && lane < 24) {
        const __nv_bfloat16* a = lane < 16 ? p.xp + (size_t)(128 * rb + 16 * j + lane) * DM + 64 * warp
                                           : p.wqkv + (size_t)(64 * warp + 4 * rb + (lane & 3)) * (3 * DM) + 512 + 128 * (lane & 4) + 64 * j;
        asm volatile("prefetch.global.L2 [%0];" ::"l"(a) : "memory");
    }
    if (warp == 8 && elect_one()) {
        TS(0); TSG(62);
        for (int i = 0; i < 13; i++) mbar_init(sb + XFULL + 8 * i, 1);
        asm volatile("fence.proxy.async.shared::cta;" ::: "memory");
#pragma unroll
        for (int k = 0; k < PRE; k++) {
            mbar_expect_tx(sb + XFULL + 8 * k, BLK);
            tma_load_2d(sb + OFF_X + k * BLK, &p.x, 64 * k, 128 * rb, sb + XFULL + 8 * k);
            mbar_expect_tx(sb + BFULL + 8 * k, BLK);
            tma_load_2d(sb + OFF_B + k * BLK, &p.qkv, 512 + 64 * j, 64 * k, sb + BFULL + 8 * k);
            tma_load_2d(sb + OFF_B + k * BLK + 8192, &p.qkv, 1024 + 64 * j, 64 * k, sb + BFULL + 8 * k);
        }
        TS(1);
    } else if (warp == 9 && elect_one()) {
        if (sb & 1023) __trap();
        for (int i = 0; i < NSLOT; i++) mbar_init(sb + BEMPTY + 8 * i, 4);
        for (int i = 0; i < 6; i++) { mbar_init(sb + GFULL + 8 * i, 2); mbar_init(sb + GEMPTY + 8 * i, 8); }
        mbar_init(sb + GREADY, 2); mbar_init(sb + EREADY, 1);
        mbar_init(sb + STGFREE, 1); mbar_init(sb + QFREE, 1); mbar_init(sb + TXOK, 1);
        for (int i = 0; i < 4; i++) { mbar_init(sb + RXFULL + 8 * i, 1); mbar_expect_tx(sb + RXFULL + 8 * i, 4096); }
        asm volatile("st.shared.u32 [%0], %1;" ::"r"(sb + OFF_EPOCH + 4), "r"(0u) : "memory");
        asm volatile("fence.mbarrier_init.release.cluster;" ::: "memory");
    }
    __syncthreads();
    asm volatile("barrier.cluster.arrive.relaxed.aligned;" ::: "memory");

    if (warp >= 8) {
        asm volatile("setmaxnreg.dec.sync.aligned.u32 40;");
        if (warp == 8) {
            if (elect_one()) {
#pragma unroll
                for (int k = PRE; k < 8; k++) {
                    if (PACE > 0 && k >= PACE) mbar_wait(sb + (k - PACE < NSLOT ? BFULL : XFULL) + 8 * (k - PACE), 0);
                    mbar_expect_tx(sb + XFULL + 8 * k, BLK);
                    tma_load_2d(sb + OFF_X + k * BLK, &p.x, 64 * k, 128 * rb, sb + XFULL + 8 * k);
                    if (k < NSLOT) {
                        mbar_expect_tx(sb + BFULL + 8 * k, BLK);
                        tma_load_2d(sb + OFF_B + k * BLK, &p.qkv, 512 + 64 * j, 64 * k, sb + BFULL + 8 * k);
                        tma_load_2d(sb + OFF_B + k * BLK + 8192, &p.qkv, 1024 + 64 * j, 64 * k, sb + BFULL + 8 * k);
                    }
                }
                TS(61);
                uint32_t s = 0, ph = 0;
#pragma unroll 1
                for (int slot = 0; slot < 5; slot++) {
                    const CUtensorMap *m0, *m1; int c0, c1;
                    slot_weights(p, slot, ct, rank, m0, m1, c0, c1);
#pragma unroll 1
                    for (int kb = slot == 0 ? 5 : 0; kb < 8; kb++) {
                        mbar_wait(sb + BEMPTY + 8 * s, ph);
                        mbar_expect_tx(sb + BFULL + 8 * s, BLK);
                        tma_load_2d(sb + OFF_B + s * BLK, m0, c0, 64 * kb, sb + BFULL + 8 * s);
                        tma_load_2d(sb + OFF_B + s * BLK + 8192, m1, c1, 64 * kb, sb + BFULL + 8 * s);
                        if (++s == NSLOT) { s = 0; ph ^= 1; }
                    }
                }
#pragma unroll
                for (int i = 0; i < 19; i++) {
                    if (i < gemm2_n(rank)) {
                        const int s = i % 6;
                        const int blk = rank ? gemm2_block(i, 1) : gemm2_block(i, 0);
                        mbar_wait(sb + GEMPTY + 8 * s, (i / 6) & 1);
                        mbar_expect_tx(sb + GFULL + 8 * s, BLK);
                        tma_load_3d(sb + gstage_off(s) + BLK, blk < 28 ? &p.wd : &p.wo, 0, 64 * (blk < 28 ? blk : blk - 28), 2 * ct, sb + GFULL + 8 * s);
                    }
                }
            }
        } else if (warp == 9) {
            if (elect_one()) {
                asm volatile("st.shared.u32 [%0], %1;" ::"r"(sb + OFF_EPOCH), "r"(ld_relaxed(g_kvcnt + 32 * j) >> 4) : "memory");
                mbar_arrive(sb + EREADY);
                mbar_wait(sb + XFULL + 8 * PF0, 0);
                if (rb < 6) tma_prefetch_2d(&p.qkv, 512 + 512 * (rb & 1) + 64 * j, 320 + 64 * (rb >> 1));
                mbar_wait(sb + XFULL + 8 * PF1, 0);
                {
                    const CUtensorMap *m0, *m1; int c0, c1;
                    slot_weights(p, 1, ct, rank, m0, m1, c0, c1);
                    tma_prefetch_2d((rb & 1) ? m1 : m0, (rb & 1) ? c1 : c0, 64 * (rb >> 1));
                }
                mbar_wait(sb + XFULL + 8 * PF2, 0);
                for (int slot = 2; slot < 5; slot++) {
                    const CUtensorMap *m0, *m1; int c0, c1;
                    slot_weights(p, slot, ct, rank, m0, m1, c0, c1);
                    tma_prefetch_2d((rb & 1) ? m1 : m0, (rb & 1) ? c1 : c0, 64 * (rb >> 1));
                }
                for (int i = rb; i < gemm2_n(rank); i += 16) {
                    const int blk = gemm2_block(i, rank);
                    if (blk < 28) tma_prefetch_3d(&p.wd, 0, 64 * blk, 2 * ct);
                    else tma_prefetch_3d(&p.wo, 0, 64 * (blk - 28), 2 * ct);
                }
                prefetch_tmap(&p.out);
            }
            __syncwarp();
            uint32_t epoch;
            asm volatile("ld.shared.u32 %0, [%1];" : "=r"(epoch) : "r"(sb + OFF_EPOCH) : "memory");
            if (lane < 17) reinterpret_cast<float4*>(&g_kvacc[(epoch + 1) & 1][0][0])[blockIdx.x * 17 + lane] = make_float4(0.f, 0.f, 0.f, 0.f);
            const int nuse = rank == 0 ? 7 : 4;
#pragma unroll 1
            for (int u = 0; u < nuse; u++) {
                bar_sync(BAR_STORE, 160);
                if (elect_one()) {
                    if (u == 0) {
                        mbar_arrive(sb + STGFREE);
                        asm volatile("fence.acq_rel.gpu;" ::: "memory");
                        asm volatile("red.relaxed.gpu.global.add.u32 [%0], %1;" ::"l"(g_kvcnt + 32 * j), "r"(1u) : "memory");
                    } else {
                        const bool isq = rank == 0 && u >= 3;
                        const int q = u - 3;
                        const int blk = isq ? 28 + 2 * ct + (q >> 1) : slot_block(u, ct, rank);
                        bulk_store(g_hbuf + (size_t)(rb * NKB2 + blk) * BLK + (isq ? (q & 1) * 8192 : 0), sb + OFF_STG, isq ? 8192 : BLK);
                        asm volatile("cp.async.bulk.commit_group;" ::: "memory");
                        asm volatile("cp.async.bulk.wait_group.read 0;" ::: "memory");
                        mbar_arrive(sb + (isq ? QFREE : STGFREE));
                        if (!isq || (q & 1)) {
                            asm volatile("cp.async.bulk.wait_group 0;" ::: "memory");
                            st_relaxed(g_flags + rb * 64 + block_flag(blk), epoch + 1);
                        }
                    }
                    TS(30 + (u < 3 ? u : u == 4 ? 7 : 3));
                }
                __syncwarp();
            }
        } else {
            mbar_wait(sb + EREADY, 0);
            uint32_t epoch;
            asm volatile("ld.shared.u32 %0, [%1];" : "=r"(epoch) : "r"(sb + OFF_EPOCH) : "memory");
            {
                const int r = 64 * (warp - 10) + lane;
                unsigned long long e0, e1;
                uint32_t n = 0;
                do {
                    asm volatile("ld.relaxed.gpu.global.u64 %0, [%1];" : "=l"(e0) : "l"(g_gate + 128 * rb + r) : "memory");
                    asm volatile("ld.relaxed.gpu.global.u64 %0, [%1];" : "=l"(e1) : "l"(g_gate + 128 * rb + r + 32) : "memory");
                    if (++n > SPIN_LIMIT) __trap();
                } while (!__all_sync(0xffffffffu, (uint32_t)(e0 >> 32) == epoch + 1 && (uint32_t)(e1 >> 32) == epoch + 1));
                asm volatile("st.shared.u32 [%0], %1;" ::"r"(sb + OFF_G + 4 * r), "r"((uint32_t)e0) : "memory");
                asm volatile("st.shared.u32 [%0], %1;" ::"r"(sb + OFF_G + 4 * r + 128), "r"((uint32_t)e1) : "memory");
                __syncwarp();
                if (lane == 0) { mbar_arrive(sb + GREADY); if (warp == 10) TS(36); }
            }
            if (warp == 11) {
                const uint32_t* fl = g_flags + rb * 64 + rank * 32 + lane;
                const uint32_t full = (1u << gemm2_n(rank)) - 1;
                uint32_t ready = 0, n = 0;
                while (ready != full) {
                    const uint32_t v = lane < gemm2_n(rank) ? ld_acquire(fl) : 0;
                    const uint32_t now = __ballot_sync(0xffffffffu, v == epoch + 1) & full;
                    if (now != ready) {
                        ready = now;
                        __syncwarp();
                        if (lane == 0) asm volatile("st.release.cta.shared.u32 [%0], %1;" ::"r"(sb + OFF_EPOCH + 4), "r"(__ffs(~now) - 1) : "memory");
                    } else {
                        __nanosleep(100);
                    }
                    if (++n > SPIN_LIMIT) __trap();
                }
            } else if (elect_one()) {
                const uint8_t* hb = g_hbuf + (size_t)rb * NKB2 * BLK;
                uint32_t have = 0;
#pragma unroll
                for (int i = 0; i < 19; i++) {
                    if (i < gemm2_n(rank)) {
                        const int s = i % 6;
                        mbar_wait(sb + GEMPTY + 8 * s, (i / 6) & 1);
                        uint32_t n = 0;
                        while (have <= i) {
                            if (n) __nanosleep(40);
                            asm volatile("ld.acquire.cta.shared.u32 %0, [%1];" : "=r"(have) : "r"(sb + OFF_EPOCH + 4) : "memory");
                            if (++n > (SPIN_LIMIT << 2)) __trap();
                        }
                        asm volatile("fence.proxy.async.global;" ::: "memory");
                        mbar_expect_tx(sb + GFULL + 8 * s, BLK);
                        const int blk = rank ? gemm2_block(i, 1) : gemm2_block(i, 0);
                        bulk_load(sb + gstage_off(s), hb + (size_t)blk * BLK, BLK, sb + GFULL + 8 * s);
                        TS(40 + i);
                    }
                }
            }
        }
    } else {
        asm volatile("setmaxnreg.inc.sync.aligned.u32 232;");
        const int wg = warp >> 2, w = warp & 3;
        const uint32_t stg = sb + OFF_STG;
        const uint32_t st_row = (uint32_t)(16 * w + (lane & 15)) * 128;
        const uint32_t st_sw = lane & 7, st_hi = lane >> 4;
        const int grow = 16 * w + (lane >> 2);

        if (wg == 1) {
            const int row0 = 128 * rb + 16 * j + 4 * w;
            const int gk = lane >> 2, cA = 2 * (lane & 3) + (gk & 1), cB = cA ^ 1;
            const uint4 wa = *reinterpret_cast<const uint4*>(p.gate_w + 64 * gk + 8 * cA);
            const uint4 wb = *reinterpret_cast<const uint4*>(p.gate_w + 64 * gk + 8 * cB);
            const uint32_t ww[8] = {wa.x, wa.y, wa.z, wa.w, wb.x, wb.y, wb.z, wb.w};
#pragma unroll
            for (int k = 7; k >= 0; k--) mbar_wait(sb + XFULL + 8 * k, 0);
            uint4 v[4][2];
#pragma unroll
            for (int r = 0; r < 4; r++) {
                const uint32_t row = 16 * j + 4 * w + r, a = sb + OFF_X + gk * BLK + row * 128;
                asm volatile("ld.shared.v4.u32 {%0,%1,%2,%3}, [%4];" : "=r"(v[r][0].x), "=r"(v[r][0].y), "=r"(v[r][0].z), "=r"(v[r][0].w)
                             : "r"(a + ((cA ^ (row & 7)) << 4)) : "memory");
                asm volatile("ld.shared.v4.u32 {%0,%1,%2,%3}, [%4];" : "=r"(v[r][1].x), "=r"(v[r][1].y), "=r"(v[r][1].z), "=r"(v[r][1].w)
                             : "r"(a + ((cB ^ (row & 7)) << 4)) : "memory");
            }
            float mine = 0.f;
#pragma unroll
            for (int r = 0; r < 4; r++) {
                const uint32_t vv[8] = {v[r][0].x, v[r][0].y, v[r][0].z, v[r][0].w, v[r][1].x, v[r][1].y, v[r][1].z, v[r][1].w};
                float s0 = 0.f, s1 = 0.f;
#pragma unroll
                for (int i = 0; i < 8; i++) {
                    s0 = fmaf(__uint_as_float(vv[i] << 16), __uint_as_float(ww[i] << 16), s0);
                    s1 = fmaf(__uint_as_float(vv[i] & 0xffff0000u), __uint_as_float(ww[i] & 0xffff0000u), s1);
                }
                float s = s0 + s1;
#pragma unroll
                for (int o = 16; o > 0; o >>= 1) s += __shfl_xor_sync(0xffffffffu, s, o);
                if (lane == r) mine = s;
            }
            mbar_wait(sb + EREADY, 0);
            uint32_t epoch;
            asm volatile("ld.shared.u32 %0, [%1];" : "=r"(epoch) : "r"(sb + OFF_EPOCH) : "memory");
            if (lane < 4) {
                const float g = ex2(-1.4426950408889634f * mine);
                const unsigned long long e = ((unsigned long long)(epoch + 1) << 32) | __float_as_uint(g);
                asm volatile("st.relaxed.gpu.global.u64 [%0], %1;" ::"l"(g_gate + row0 + lane), "l"(e) : "memory");
            }
            if (threadIdx.x == 128) TS(35);
        }

        uint32_t sc[4];
        for (int slot = wg; slot < 4; slot += 2) {
            float acc[2][64];
            if (slot > 0) bar_sync(wg == 0 ? BAR_ORDER0 : BAR_ORDER1, 256);
            const uint32_t prev = tile_mainloop<false>(acc, sb, slot, wg, lane);
            wgmma_wait<0>();
            fence_regs(acc[0]); fence_regs(acc[1]);
            if (lane == 0) {
                mbar_arrive(sb + BEMPTY + 8 * prev);
                if (slot == 3) for (int i = 0; i < 6; i++) mbar_arrive(sb + GEMPTY + 8 * i);
            }
            if ((threadIdx.x & 127) == 0) TS(4 + 4 * slot);

            if (slot == 0) {
                float d[36];
                asm volatile("st.shared.v4.u32 [%0], {%1,%1,%1,%1};" ::"r"(sb + OFF_ONES + threadIdx.x * 16), "r"(0x3f803f80u) : "memory");
#define STS_V(b, jp) stsm_x4(stg + 8192 + st_row + (((2 * (jp) + st_hi) ^ st_sw) << 4), pack2(acc[b][32 + 8 * (jp)], acc[b][33 + 8 * (jp)]), \
                             pack2(acc[b][34 + 8 * (jp)], acc[b][35 + 8 * (jp)]), pack2(acc[b][36 + 8 * (jp)], acc[b][37 + 8 * (jp)]),      \
                             pack2(acc[b][38 + 8 * (jp)], acc[b][39 + 8 * (jp)]))
#define PHI_K(r, b, jp) _Pragma("unroll") for (int i = 0; i < 4; i++) r[i] = phi2(acc[b][8 * (jp) + 2 * i], acc[b][8 * (jp) + 2 * i + 1], l2e)
#define STS_K(r, jp) stsm_x4(stg + st_row + (((2 * (jp) + st_hi) ^ st_sw) << 4), r[0], r[1], r[2], r[3])
#define KV_MMA(b)                                                                                        \
    asm volatile("fence.proxy.async.shared::cta;" ::: "memory");                                         \
    bar_sync(BAR_WG0, 128);                                                                              \
    if (threadIdx.x == 0) TS(64 + 4 * b);                                                                \
    wgmma_fence();                                                                                       \
    _Pragma("unroll") for (int t = 0; t < 4; t++) {                                                      \
        const uint64_t db = desc_b(stg + 8192 + t * 2048, OFF_ONES - OFF_STG - 8192 - t * 2048);         \
        if (b == 0 && t == 0) wgmma_n72_tt<false>(d, desc_b(stg + t * 2048), db);                        \
        else wgmma_n72_tt<true>(d, desc_b(stg + t * 2048), db);                                          \
    }                                                                                                    \
    wgmma_commit();                                                                                      \
    if (threadIdx.x == 0) TS(65 + 4 * b);
                uint32_t k0[4], k1[4], k2[4], k3[4];
                STS_V(0, 0); STS_V(0, 1); STS_V(0, 2); STS_V(0, 3);
                float l2e = sched_fence(sb);
                PHI_K(k0, 0, 0); PHI_K(k1, 0, 1); STS_K(k0, 0); STS_K(k1, 1);
                l2e = sched_fence(sb);
                PHI_K(k2, 0, 2); STS_K(k2, 2);
                l2e = sched_fence(sb);
                PHI_K(k3, 0, 3); STS_K(k3, 3);
                KV_MMA(0)
                PHI_K(k0, 1, 0); PHI_K(k1, 1, 1);
                if (threadIdx.x == 0) TS(66);
                wgmma_wait<0>();
                bar_sync(BAR_WG0, 128);
                if (threadIdx.x == 0) TS(67);
                STS_K(k0, 0); STS_K(k1, 1);
                STS_V(1, 0); STS_V(1, 1); STS_V(1, 2); STS_V(1, 3);
                l2e = sched_fence(sb);
                PHI_K(k2, 1, 2); PHI_K(k3, 1, 3); STS_K(k2, 2); STS_K(k3, 3);
                KV_MMA(1)
#undef STS_V
#undef PHI_K
#undef STS_K
#undef KV_MMA
                mbar_wait(sb + EREADY, 0);
                uint32_t epoch;
                asm volatile("ld.shared.u32 %0, [%1];" : "=r"(epoch) : "r"(sb + OFF_EPOCH) : "memory");
                float* dst = &g_kvacc[epoch & 1][4 * j + w][0];
                wgmma_wait<0>();
                fence_regs(d);
                if (threadIdx.x == 0) TS(70);
                float c[8];
#pragma unroll
                for (int i = 0; i < 8; i++) c[i] = w == 0 ? d[i] : w == 1 ? d[8 + i] : w == 2 ? d[16 + i] : d[24 + i];
                red_add_v4(dst + lane * 8, c[0], c[1], c[2], c[3]);
                red_add_v4(dst + lane * 8 + 4, c[4], c[5], c[6], c[7]);
                if ((lane & 3) < 2)
                    asm volatile("red.relaxed.gpu.global.add.f32 [%0], %1;" ::"l"(dst + 256 + (lane >> 2) + 8 * (lane & 1)), "f"((lane & 1) ? d[34] : d[32]) : "memory");
            } else if (slot == 3 && rank == 0) {
                uint32_t a[2][2][4];
#define PACK_Q(buf, step)                                                                                     \
    _Pragma("unroll") for (int u = 0; u < 2; u++) {                                                           \
        const float* q = &acc[((step) >> 1) & 1][32 * ((step) >> 2) + 16 * ((step) & 1) + 8 * u];             \
        _Pragma("unroll") for (int i = 0; i < 4; i++) a[buf][u][i] = phi2(q[2 * i], q[2 * i + 1]);            \
    }
                {
                    uint32_t epoch;
                    asm volatile("ld.shared.u32 %0, [%1];" : "=r"(epoch) : "r"(sb + OFF_EPOCH) : "memory");
                    wait_count(g_kvcnt + 32 * (j + (w >> 1)), (epoch + 1) << 4);
                    const float* src = &g_kvacc[epoch & 1][8 * ct + 2 * w][0];
                    float4 u[2][2];
                    uint32_t z[2][2];
#pragma unroll
                    for (int h = 0; h < 2; h++) {
                        u[h][0] = ld_cg4(src + h * 272 + lane * 8);
                        u[h][1] = ld_cg4(src + h * 272 + lane * 8 + 4);
                        z[h][0] = ld_relaxed(reinterpret_cast<const uint32_t*>(src + h * 272 + 256 + (lane >> 2)));
                        z[h][1] = ld_relaxed(reinterpret_cast<const uint32_t*>(src + h * 272 + 264 + (lane >> 2)));
                    }
                    PACK_Q(0, 0)
                    mbar_wait(sb + STGFREE, 0);
#pragma unroll
                    for (int h = 0; h < 2; h++) {
                        const uint32_t f[6] = {pack2(u[h][0].x, u[h][0].y), pack2(u[h][0].z, u[h][0].w), pack2(u[h][1].x, u[h][1].y),
                                               pack2(u[h][1].z, u[h][1].w), pack2(__uint_as_float(z[h][0]), __uint_as_float(z[h][0])),
                                               pack2(__uint_as_float(z[h][1]), __uint_as_float(z[h][1]))};
#pragma unroll
                        for (int i = 0; i < 6; i++)
                            asm volatile("st.shared.u32 [%0], %1;" ::"r"(stg + 8192 + (2 * w + h) * 768 + i * 128 + lane * 4), "r"(f[i]) : "memory");
                    }
                    asm volatile("fence.proxy.async.shared::cta;" ::: "memory");
                    bar_sync(BAR_WG1, 128);
                    if (threadIdx.x == 128) TS(38);
                }
                float g[4], ge[4];
#pragma unroll
                for (int i = 0; i < 4; i++) {
                    g[i] = 1.f + lds_f32(sb + OFF_G + 4 * (64 * (i >> 1) + grow + 8 * (i & 1)));
                    ge[i] = g[i] * 1e-6f;
                }
                const uint64_t dkv = (uint64_t)((((stg + 8192) & 0x3FFFF) >> 4) | (8u << 16)) | ((uint64_t)16u << 32);
#pragma unroll
                for (int step = 0; step < 8; step++) {
                    const int b = (step >> 1) & 1, h0 = 4 * (step >> 2) + 2 * (step & 1);
                    float d[2][12];
                    wgmma_fence();
                    wgmma_n24_rs(d[0], a[step & 1][0], dkv + 48 * h0);
                    wgmma_n24_rs(d[1], a[step & 1][1], dkv + 48 * (h0 + 1));
                    wgmma_commit();
                    if (step < 7) { PACK_Q((step + 1) & 1, step + 1) }
                    wgmma_wait<0>();
                    if (step > 0 && !(step & 1)) mbar_wait(sb + QFREE, ((step >> 1) - 1) & 1);
#pragma unroll
                    for (int u = 0; u < 2; u++) {
                        fence_regs(d[u]);
                        const float r0 = rcp(fmaf(d[u][8], g[2 * b], ge[2 * b])), r1 = rcp(fmaf(d[u][10], g[2 * b + 1], ge[2 * b + 1]));
                        stsm_x4(stg + st_row + (((2 * ((h0 + u) & 3) + st_hi) ^ st_sw) << 4),
                                pack2(d[u][0] * r0, d[u][1] * r0), pack2(d[u][2] * r1, d[u][3] * r1),
                                pack2(d[u][4] * r0, d[u][5] * r0), pack2(d[u][6] * r1, d[u][7] * r1));
                    }
                    if (step & 1) {
                        asm volatile("fence.proxy.async.shared::cta;" ::: "memory");
                        if (step < 7) bar_arrive(BAR_STORE, 160);
                    }
                }
#undef PACK_Q
            } else {
                if (slot < 3) {
                    mbar_wait(sb + GREADY, 0);
    #pragma unroll
                    for (int i = 0; i < 4; i++) {
                        const float f = 1.f - rcp(1.f + lds_f32(sb + OFF_G + 4 * (64 * (i >> 1) + grow + 8 * (i & 1))));
                        sc[i] = pack2(f, f);
                    }
                }
                mbar_wait(sb + STGFREE, (slot - 1) & 1);
#pragma unroll
                for (int b = 0; b < 2; b++) {
#pragma unroll
                    for (int jp = 0; jp < 4; jp++) {
                        const float* g = &acc[b][8 * jp];
                        const float* u = &acc[b][32 + 8 * jp];
                        stsm_x4(stg + b * 8192 + st_row + (((2 * jp + st_hi) ^ st_sw) << 4),
                                hmul2(pack2(g[0] * u[0], g[1] * u[1]), sc[2 * b]), hmul2(pack2(g[2] * u[2], g[3] * u[3]), sc[2 * b + 1]),
                                hmul2(pack2(g[4] * u[4], g[5] * u[5]), sc[2 * b]), hmul2(pack2(g[6] * u[6], g[7] * u[7]), sc[2 * b + 1]));
                    }
                }
                asm volatile("fence.proxy.async.shared::cta;" ::: "memory");
            }
            bar_arrive(BAR_STORE, 160);
            if ((threadIdx.x & 127) == 0) TS(5 + 4 * slot);
        }

        if (wg == 0) {
            float acc[2][64];
            float (&accS)[64] = acc[0];
            float (&accK)[64] = acc[1];
            asm volatile("barrier.cluster.wait.aligned;" ::: "memory");
            bar_sync(BAR_ORDER0, 256);
            tile_mainloop<true>(acc, __shfl_sync(0xffffffffu, sb, 0), 4, 0, lane);
            const int nblk = gemm2_n(rank);
            const uint64_t dS = desc_a(sb + (rank ^ 1) * 8192), dK = desc_a(sb + rank * 8192), dB = desc_b(sb + BLK);
            uint32_t s = 1, ph = 0;
            int64_t off = 2048;
            TW_DECL();
            {
                uint32_t h[2][16];
#define PACK_H(b)                                                                                             \
    _Pragma("unroll") for (int i = 0; i < 16; i++)                                                            \
        h[b][i] = hmul2(pack2(acc[b][2 * i] * acc[b][32 + 2 * i], acc[b][2 * i + 1] * acc[b][33 + 2 * i]), sc[2 * (b) + (i & 1)]); \
    _Pragma("unroll") for (int i = 0; i < 16; i++) asm volatile("" : "+r"(h[b][i])::"memory");
                mbar_wait(sb + GFULL, 0);
                wgmma_wait<1>();
                fence_regs(acc[0]);
                if (threadIdx.x == 0) TS(59);
                PACK_H(0)
                wgmma_fence();
                wgmma_n128_restart(accS, dS, dB);
                wgmma_n128(accS, dS + 2, dB + 128);
                wgmma_n128(accS, dS + 4, dB + 256);
                wgmma_n128(accS, dS + 6, dB + 384);
                wgmma_commit();
                wgmma_wait<1>();
                fence_regs(acc[1]);
                if (threadIdx.x == 0) TS(20);
                if (lane == 0) mbar_arrive(sb + GEMPTY + 40);
                PACK_H(1)
#undef PACK_H
                wgmma_fence();
                wgmma_n128_restart(accK, dK, dB);
                wgmma_commit();
                bar_sync(BAR_WG0, 128);
#pragma unroll
                for (int k = 1; k < 4; k++) {
#pragma unroll
                    for (int t = 3 * (k - 1); t < 3 * k && t < 8; t++)
                        stsm_x4(sb + OFF_RX + (t >> 2) * 8192 + st_row + (((2 * (t & 3) + st_hi) ^ st_sw) << 4),
                                h[t >> 2][4 * (t & 3)], h[t >> 2][4 * (t & 3) + 1], h[t >> 2][4 * (t & 3) + 2], h[t >> 2][4 * (t & 3) + 3]);
                    if (k == 3) mbar_wait(sb + GFULL + 8, 0);
                    wgmma_fence();
                    wgmma_n128(accK, dK + 2 * k, dB + 128 * k);
                    wgmma_commit();
                }
            }
#define G2_NEXT() do { off += s == 0 ? 2048 : s == 5 ? -6144 : (s & 1) ? 6144 : -4096; if (++s == 6) { s = 0; ph ^= 1; } } while (0)
#pragma unroll 1
            for (int i = 1; i < nblk - TAIL_LEAD; i++) {
                const uint64_t aS = dS + off, aK = dK + off, db = dB + off;
                wgmma_fence();
                wgmma_n128(accS, aS, db);
                wgmma_n128(accK, aK, db);
                wgmma_n128(accS, aS + 2, db + 128);
                wgmma_n128(accK, aK + 2, db + 128);
                wgmma_commit();
                wgmma_wait<1>();
                if (lane == 0) mbar_arrive2(sb + GEMPTY + 8 * (s == 0 ? 5 : s - 1));
                if (i == STI) {
                    asm volatile("fence.proxy.async.shared::cta;" ::: "memory");
                    bar_sync(BAR_WG0, 128);
                    if (threadIdx.x == 0) {
                        bulk_store(g_hbuf + (size_t)(rb * NKB2 + slot_block(4, ct, rank)) * BLK, sb + OFF_RX, BLK);
                        asm volatile("cp.async.bulk.commit_group;" ::: "memory");
                        TS(21);
                    }
                } else if (i == 4 && threadIdx.x == 0) {
                    uint32_t epoch;
                    asm volatile("ld.shared.u32 %0, [%1];" : "=r"(epoch) : "r"(sb + OFF_EPOCH) : "memory");
                    asm volatile("cp.async.bulk.wait_group 0;" ::: "memory");
                    st_relaxed(g_flags + rb * 64 + block_flag(slot_block(4, ct, rank)), epoch + 1);
                    mbar_arrive_remote(mapa(sb + TXOK, rank ^ 1));
                    TS(34);
                }
                __syncwarp();
                wgmma_fence();
                wgmma_n128(accS, aS + 4, db + 256);
                wgmma_n128(accK, aK + 4, db + 256);
                wgmma_commit();
                G2_NEXT();
                { TW_BEGIN(); mbar_wait(sb + GFULL + 8 * s, ph); TW_END(twait); }
                wgmma_fence();
                wgmma_n128(accS, aS + 6, db + 384);
                wgmma_n128(accK, aK + 6, db + 384);
                wgmma_commit();
            }
            int64_t offs[TAIL_LEAD];
#pragma unroll
            for (int t = 0; t < TAIL_LEAD; t++) {
                offs[t] = off;
                wgmma_fence();
                wgmma_n128(accS, dS + off, dB + off);
                wgmma_n128(accS, dS + off + 2, dB + off + 128);
                wgmma_commit();
                if (t == 0) {
                    wgmma_wait<1>();
                    if (TAIL_LEAD < 6 && lane == 0) mbar_arrive2(sb + GEMPTY + 8 * (s == 0 ? 5 : s - 1));
                }
                const int64_t cur = off;
                wgmma_fence();
                wgmma_n128(accS, dS + cur + 4, dB + cur + 256);
                wgmma_commit();
                if (t + 1 < TAIL_LEAD) { G2_NEXT(); TW_BEGIN(); mbar_wait(sb + GFULL + 8 * s, ph); TW_END(twait); }
                wgmma_fence();
                wgmma_n128(accS, dS + cur + 6, dB + cur + 384);
                wgmma_commit();
            }
#undef G2_NEXT
            if (threadIdx.x == 0) TSV(29, twait);
            const uint32_t rx = sb + OFF_RX + w * 4096 + lane * 16;
            const uint32_t dst = mapa(rx, rank ^ 1), bar = mapa(sb + RXFULL + 8 * w, rank ^ 1);
            mbar_wait(sb + TXOK, 0);
            wgmma_fence();
            wgmma_n128(accK, dK + offs[0], dB + offs[0]);
            wgmma_n128(accK, dK + offs[0] + 2, dB + offs[0] + 128);
            wgmma_commit();
            wgmma_wait<1>();
            fence_regs(accS);
            if (threadIdx.x == 0) TS(27);
#pragma unroll
            for (int m = 2; m < 4 * TAIL_LEAD; m++) {
                if (m < 10) {
                    const float* o = &accS[8 * (m - 2)];
                    asm volatile("st.async.weak.shared::cluster.mbarrier::complete_tx::bytes.v4.b32 [%0], {%1,%2,%3,%4}, [%5];"
                                 ::"r"(dst + (m - 2) * 512), "r"(pack2(o[0], o[1])), "r"(pack2(o[2], o[3])), "r"(pack2(o[4], o[5])),
                                   "r"(pack2(o[6], o[7])), "r"(bar) : "memory");
                }
                wgmma_fence();
                wgmma_n128(accK, dK + offs[m >> 2] + 2 * (m & 3), dB + offs[m >> 2] + 128 * (m & 3));
                wgmma_commit();
                if (m == 10 && threadIdx.x == 0) TS(28);
            }
            mbar_wait(sb + RXFULL + 8 * w, 0);
            if (threadIdx.x == 0) TS(24);
            uint32_t v[8][4];
#pragma unroll
            for (int i = 0; i < 8; i++)
                asm volatile("ld.shared.v4.u32 {%0,%1,%2,%3}, [%4];" : "=r"(v[i][0]), "=r"(v[i][1]), "=r"(v[i][2]), "=r"(v[i][3]) : "r"(rx + i * 512) : "memory");
            __syncwarp();
            wgmma_wait<0>();
            fence_regs(accK);
            if (threadIdx.x == 0) TS(23);
            const uint32_t ob = sb + OFF_RX + w * 4096 + (uint32_t)(lane & 15) * 128;
#pragma unroll
            for (int jp = 0; jp < 8; jp++) {
                const float* o = &accK[8 * jp];
                uint32_t r[4];
#pragma unroll
                for (int i = 0; i < 4; i++) {
                    asm("add.rn.bf16x2 %0, %1, %2;" : "=r"(r[i]) : "r"(pack2(o[2 * i], o[2 * i + 1])), "r"(v[jp][i]));
                }
                stsm_x4(ob + (jp >> 2) * 2048 + (((2 * (jp & 3) + st_hi) ^ st_sw) << 4), r[0], r[1], r[2], r[3]);
            }
            asm volatile("fence.proxy.async.shared::cta;" ::: "memory");
            __syncwarp();
            if (elect_one()) {
                tma_store_3d(&p.out, sb + OFF_RX + w * 4096, 0, 128 * rb + 64 * rank + 16 * w, 2 * ct);
                asm volatile("cp.async.bulk.commit_group;" ::: "memory");
                asm volatile("cp.async.bulk.wait_group.read 0;" ::: "memory");
                if (w == 0) { TS(25); TSG(63); }
            }
        }
    }
}

typedef CUresult (*EncodeFn)(CUtensorMap*, CUtensorMapDataType, cuuint32_t, void*, const cuuint64_t*, const cuuint64_t*,
                             const cuuint32_t*, const cuuint32_t*, CUtensorMapInterleave, CUtensorMapSwizzle,
                             CUtensorMapL2promotion, CUtensorMapFloatOOBfill);

void make_2d(EncodeFn enc, CUtensorMap* m, const void* ptr, uint64_t rows, uint64_t cols, uint32_t brows) {
    cuuint64_t dims[2] = {cols, rows};
    cuuint64_t strides[1] = {cols * 2};
    cuuint32_t box[2] = {64, brows};
    cuuint32_t es[2] = {1, 1};
    CUresult r = enc(m, CU_TENSOR_MAP_DATA_TYPE_BFLOAT16, 2, const_cast<void*>(ptr), dims, strides, box, es,
                     CU_TENSOR_MAP_INTERLEAVE_NONE, CU_TENSOR_MAP_SWIZZLE_128B, L2PROMO,
                     CU_TENSOR_MAP_FLOAT_OOB_FILL_NONE);
    if (r != CUDA_SUCCESS) fprintf(stderr, "tensor map 2d failed: %d\n", (int)r);
}
void make_3d(EncodeFn enc, CUtensorMap* m, const void* ptr, uint64_t rows, uint64_t cols, uint32_t brows) {
    cuuint64_t dims[3] = {64, rows, cols / 64};
    cuuint64_t strides[2] = {cols * 2, 128};
    cuuint32_t box[3] = {64, brows, 2};
    cuuint32_t es[3] = {1, 1, 1};
    CUresult r = enc(m, CU_TENSOR_MAP_DATA_TYPE_BFLOAT16, 3, const_cast<void*>(ptr), dims, strides, box, es,
                     CU_TENSOR_MAP_INTERLEAVE_NONE, CU_TENSOR_MAP_SWIZZLE_128B, L2PROMO,
                     CU_TENSOR_MAP_FLOAT_OOB_FILL_NONE);
    if (r != CUDA_SUCCESS) fprintf(stderr, "tensor map 3d failed: %d\n", (int)r);
}

}

extern "C" void kernel_launch(void* const* d_in, const int* in_sizes, int n_in, void* d_out, int out_size) {
    (void)in_sizes; (void)n_in; (void)out_size;
    static EncodeFn enc = nullptr;
    if (!enc) {
        void* fn = nullptr;
        cudaDriverEntryPointQueryResult qr;
        cudaGetDriverEntryPoint("cuTensorMapEncodeTiled", &fn, cudaEnableDefault, &qr);
        enc = (EncodeFn)fn;
        cudaFuncSetAttribute(fused_kernel, cudaFuncAttributeMaxDynamicSharedMemorySize, SMEM_BYTES);
    }
    Params p;
    make_2d(enc, &p.x, d_in[0], SEQ, DM, 128);
    make_2d(enc, &p.qkv, d_in[1], DM, 3 * DM, 64);
    make_3d(enc, &p.wo, d_in[2], DM, DM, 64);
    make_2d(enc, &p.wg, d_in[4], DM, FF, 64);
    make_2d(enc, &p.wu, d_in[5], DM, FF, 64);
    make_3d(enc, &p.wd, d_in[6], FF, DM, 64);
    make_3d(enc, &p.out, d_out, SEQ, DM, 16);
    p.gate_w = (const __nv_bfloat16*)d_in[7];
    p.xp = (const __nv_bfloat16*)d_in[0];
    p.wqkv = (const __nv_bfloat16*)d_in[1];
    fused_kernel<<<128, 384, SMEM_BYTES, cudaStreamPerThread>>>(p);
}
```

```cpp
#include <cuda_runtime.h>
#include <cuda_bf16.h>
#include <cuda.h>
#include <stdint.h>
#include <stdio.h>

namespace {

constexpr int SEQ = 2048, DM = 512, FF = 1792;
constexpr int NKB2 = 36;
constexpr uint32_t BLK = 16384;

constexpr uint32_t OFF_X = 0;
constexpr int NSLOT = 5;
constexpr uint32_t OFF_B = 131072;
constexpr uint32_t OFF_RX = 196608;
constexpr uint32_t OFF_STG = 212992;
constexpr uint32_t OFF_ONES = 229376;
constexpr uint32_t OFF_G = 231424;
constexpr uint32_t OFF_BAR = 231936;
constexpr uint32_t XFULL = OFF_BAR;
constexpr uint32_t BFULL = XFULL + 64;
constexpr uint32_t BEMPTY = BFULL + 40;
constexpr uint32_t GFULL = BEMPTY + 40;
constexpr uint32_t GEMPTY = GFULL + 48;
constexpr uint32_t GOK = GEMPTY + 48;
constexpr uint32_t RETRY = GOK + 48;
constexpr uint32_t GREADY = RETRY + 8;
constexpr uint32_t EREADY = GREADY + 8;
constexpr uint32_t STGFREE = EREADY + 8;
constexpr uint32_t H4RDY = STGFREE + 24;
constexpr uint32_t KVREADY = H4RDY + 8;
constexpr uint32_t TXOK = KVREADY + 8;
constexpr uint32_t RXFULL = TXOK + 8;
constexpr uint32_t OFF_EPOCH = RXFULL + 32;
constexpr uint32_t SMEM_BYTES = OFF_EPOCH + 8;

constexpr int BAR_ORDER0 = 1, BAR_ORDER1 = 2, BAR_WG0 = 3, BAR_WG1 = 4, BAR_STORE = 5;
constexpr int TAIL_LEAD = 5;

__device__ __align__(1024) uint8_t g_hbuf[16 * NKB2 * BLK];
__device__ __align__(128) uint32_t g_flags[16 * 64];
__device__ uint32_t g_kvcnt[8 * 32];
__device__ __align__(128) float g_kvacc[2][32][272];
__device__ unsigned long long g_gate[SEQ];

constexpr uint32_t SPIN_LIMIT = 1u << 22;

__device__ __forceinline__ uint32_t smem_u32(const void* p) { return (uint32_t)__cvta_generic_to_shared(p); }
__device__ __forceinline__ void mbar_init(uint32_t bar, uint32_t cnt) {
    asm volatile("mbarrier.init.shared::cta.b64 [%0], %1;" ::"r"(bar), "r"(cnt) : "memory");
}
__device__ __forceinline__ void mbar_expect_tx(uint32_t bar, uint32_t bytes) {
    asm volatile("mbarrier.arrive.expect_tx.shared::cta.b64 _, [%0], %1;" ::"r"(bar), "r"(bytes) : "memory");
}
__device__ __forceinline__ void mbar_arrive(uint32_t bar) {
    asm volatile("mbarrier.arrive.shared::cta.b64 _, [%0];" ::"r"(bar) : "memory");
}
__device__ __forceinline__ void mbar_arrive2(uint32_t bar) {
    asm volatile("mbarrier.arrive.shared::cta.b64 _, [%0], 2;" ::"r"(bar) : "memory");
}
__device__ __forceinline__ uint32_t mapa(uint32_t addr, uint32_t cta) {
    uint32_t r;
    asm volatile("mapa.shared::cluster.u32 %0, %1, %2;" : "=r"(r) : "r"(addr), "r"(cta));
    return r;
}
__device__ __forceinline__ void mbar_arrive_remote(uint32_t remote_bar) {
    asm volatile("mbarrier.arrive.shared::cluster.b64 _, [%0];" ::"r"(remote_bar) : "memory");
}
__device__ __forceinline__ void mbar_wait(uint32_t bar, uint32_t parity) {
    asm volatile("{\n.reg .pred p;\n.reg .u32 n;\nmov.u32 n, 0;\nWAIT_LOOP:\n"
                 "mbarrier.try_wait.parity.shared::cta.b64 p, [%0], %1;\n@p bra WAIT_DONE;\n"
                 "add.u32 n, n, 1;\nsetp.lt.u32 p, n, 0x400000;\n@p bra WAIT_LOOP;\ntrap;\nWAIT_DONE:\n}" ::"r"(bar), "r"(parity) : "memory");
}
__device__ __forceinline__ void bar_sync(int id, int n) { asm volatile("bar.sync %0, %1;" ::"r"(id), "r"(n) : "memory"); }
__device__ __forceinline__ void bar_arrive(int id, int n) { asm volatile("bar.arrive %0, %1;" ::"r"(id), "r"(n) : "memory"); }

__device__ __forceinline__ void tma_load_2d(uint32_t dst, const CUtensorMap* tm, int c0, int c1, uint32_t bar) {
    asm volatile("cp.async.bulk.tensor.2d.shared::cluster.global.mbarrier::complete_tx::bytes [%0], [%1, {%3, %4}], [%2];"
                 ::"r"(dst), "l"(tm), "r"(bar), "r"(c0), "r"(c1) : "memory");
}
__device__ __forceinline__ void tma_load_3d(uint32_t dst, const CUtensorMap* tm, int c0, int c1, int c2, uint32_t bar) {
    asm volatile("cp.async.bulk.tensor.3d.shared::cluster.global.mbarrier::complete_tx::bytes [%0], [%1, {%3, %4, %5}], [%2];"
                 ::"r"(dst), "l"(tm), "r"(bar), "r"(c0), "r"(c1), "r"(c2) : "memory");
}
__device__ __forceinline__ void tma_prefetch_2d(const CUtensorMap* tm, int c0, int c1) {
    asm volatile("cp.async.bulk.prefetch.tensor.2d.L2.global.tile [%0, {%1, %2}];" ::"l"(tm), "r"(c0), "r"(c1) : "memory");
}
__device__ __forceinline__ void tma_prefetch_3d(const CUtensorMap* tm, int c0, int c1, int c2) {
    asm volatile("cp.async.bulk.prefetch.tensor.3d.L2.global.tile [%0, {%1, %2, %3}];" ::"l"(tm), "r"(c0), "r"(c1), "r"(c2) : "memory");
}
__device__ __forceinline__ void tma_store_3d(const CUtensorMap* tm, uint32_t src, int c0, int c1, int c2) {
    asm volatile("cp.async.bulk.tensor.3d.global.shared::cta.bulk_group [%0, {%2, %3, %4}], [%1];"
                 ::"l"(tm), "r"(src), "r"(c0), "r"(c1), "r"(c2) : "memory");
}
__device__ __forceinline__ void bulk_load(uint32_t dst, const void* src, uint32_t bytes, uint32_t bar) {
    asm volatile("cp.async.bulk.shared::cluster.global.mbarrier::complete_tx::bytes [%0], [%1], %2, [%3];"
                 ::"r"(dst), "l"(src), "r"(bytes), "r"(bar) : "memory");
}
__device__ __forceinline__ void bulk_store(void* dst, uint32_t src, uint32_t bytes) {
    asm volatile("cp.async.bulk.global.shared::cta.bulk_group [%0], [%1], %2;" ::"l"(dst), "r"(src), "r"(bytes) : "memory");
}
__device__ __forceinline__ void prefetch_tmap(const CUtensorMap* tm) {
    asm volatile("prefetch.tensormap [%0];" ::"l"(tm) : "memory");
}
__device__ __forceinline__ uint32_t ld_acquire(const uint32_t* p) {
    uint32_t v;
    asm volatile("ld.acquire.gpu.global.u32 %0, [%1];" : "=r"(v) : "l"(p) : "memory");
    return v;
}
__device__ __forceinline__ uint32_t ld_relaxed(const uint32_t* p) {
    uint32_t v;
    asm volatile("ld.relaxed.gpu.global.u32 %0, [%1];" : "=r"(v) : "l"(p) : "memory");
    return v;
}
__device__ __forceinline__ void wait_count(const uint32_t* p, uint32_t target) {
    asm volatile("{\n.reg .pred p;\n.reg .u32 n, v;\nmov.u32 n, 0;\nCNT_LOOP:\n"
                 "ld.acquire.gpu.global.u32 v, [%0];\nsub.u32 v, v, %1;\nsetp.ge.s32 p, v, 0;\n@p bra CNT_DONE;\n"
                 "add.u32 n, n, 1;\nsetp.lt.u32 p, n, 0x400000;\n@p bra CNT_LOOP;\ntrap;\nCNT_DONE:\n}" ::"l"(p), "r"(target) : "memory");
}
__device__ __forceinline__ void st_relaxed(uint32_t* p, uint32_t v) {
    asm volatile("st.relaxed.gpu.global.u32 [%0], %1;" ::"l"(p), "r"(v) : "memory");
}
__device__ __forceinline__ void red_add_v4(float* p, float a, float b, float c, float d) {
    asm volatile("red.relaxed.gpu.global.add.v4.f32 [%0], {%1, %2, %3, %4};" ::"l"(p), "f"(a), "f"(b), "f"(c), "f"(d) : "memory");
}
__device__ __forceinline__ float4 ld_cg4(const float* p) {
    float4 v;
    asm volatile("ld.relaxed.gpu.global.v4.f32 {%0, %1, %2, %3}, [%4];" : "=f"(v.x), "=f"(v.y), "=f"(v.z), "=f"(v.w) : "l"(p) : "memory");
    return v;
}
__device__ __forceinline__ void wgmma_fence() { asm volatile("wgmma.fence.sync.aligned;" ::: "memory"); }
__device__ __forceinline__ void wgmma_commit() { asm volatile("wgmma.commit_group.sync.aligned;" ::: "memory"); }
template <int N> __device__ __forceinline__ void wgmma_wait() { asm volatile("wgmma.wait_group.sync.aligned %0;" ::"n"(N) : "memory"); }

__device__ __forceinline__ uint64_t desc_a(uint32_t addr) {
    return (uint64_t)(((addr & 0x3FFFF) >> 4) | (1u << 16)) | ((uint64_t)(64u | (1u << 30)) << 32);
}
__device__ __forceinline__ uint64_t desc_b(uint32_t addr, uint32_t lbo = 8192) {
    return (uint64_t)(((addr & 0x3FFFF) >> 4) | ((lbo >> 4) << 16)) | ((uint64_t)(64u | (1u << 30)) << 32);
}
#define ACC8(a, o) "+f"(a[o + 0]), "+f"(a[o + 1]), "+f"(a[o + 2]), "+f"(a[o + 3]), "+f"(a[o + 4]), "+f"(a[o + 5]), "+f"(a[o + 6]), "+f"(a[o + 7])
__device__ __forceinline__ void wgmma_n128(float (&d)[64], uint64_t da, uint64_t db) {
    asm volatile("wgmma.mma_async.sync.aligned.m64n128k16.f32.bf16.bf16 "
                 "{%0,%1,%2,%3,%4,%5,%6,%7,%8,%9,%10,%11,%12,%13,%14,%15,%16,%17,%18,%19,%20,%21,%22,%23,%24,%25,%26,%27,%28,%29,%30,%31,"
                 "%32,%33,%34,%35,%36,%37,%38,%39,%40,%41,%42,%43,%44,%45,%46,%47,%48,%49,%50,%51,%52,%53,%54,%55,%56,%57,%58,%59,%60,%61,%62,%63},"
                 " %64, %65, 1, 1, 1, 0, 1;"
                 : ACC8(d, 0), ACC8(d, 8), ACC8(d, 16), ACC8(d, 24), ACC8(d, 32), ACC8(d, 40), ACC8(d, 48), ACC8(d, 56)
                 : "l"(da), "l"(db));
}
#define OUT8(a, o) "=f"(a[o + 0]), "=f"(a[o + 1]), "=f"(a[o + 2]), "=f"(a[o + 3]), "=f"(a[o + 4]), "=f"(a[o + 5]), "=f"(a[o + 6]), "=f"(a[o + 7])
__device__ __forceinline__ void wgmma_n128_first(float (&d)[64], uint64_t da, uint64_t db) {
    asm volatile("wgmma.mma_async.sync.aligned.m64n128k16.f32.bf16.bf16 "
                 "{%0,%1,%2,%3,%4,%5,%6,%7,%8,%9,%10,%11,%12,%13,%14,%15,%16,%17,%18,%19,%20,%21,%22,%23,%24,%25,%26,%27,%28,%29,%30,%31,"
                 "%32,%33,%34,%35,%36,%37,%38,%39,%40,%41,%42,%43,%44,%45,%46,%47,%48,%49,%50,%51,%52,%53,%54,%55,%56,%57,%58,%59,%60,%61,%62,%63},"
                 " %64, %65, 0, 1, 1, 0, 1;"
                 : OUT8(d, 0), OUT8(d, 8), OUT8(d, 16), OUT8(d, 24), OUT8(d, 32), OUT8(d, 40), OUT8(d, 48), OUT8(d, 56)
                 : "l"(da), "l"(db));
}
__device__ __forceinline__ void wgmma_n128_restart(float (&d)[64], uint64_t da, uint64_t db) {
    asm volatile("wgmma.mma_async.sync.aligned.m64n128k16.f32.bf16.bf16 "
                 "{%0,%1,%2,%3,%4,%5,%6,%7,%8,%9,%10,%11,%12,%13,%14,%15,%16,%17,%18,%19,%20,%21,%22,%23,%24,%25,%26,%27,%28,%29,%30,%31,"
                 "%32,%33,%34,%35,%36,%37,%38,%39,%40,%41,%42,%43,%44,%45,%46,%47,%48,%49,%50,%51,%52,%53,%54,%55,%56,%57,%58,%59,%60,%61,%62,%63},"
                 " %64, %65, 0, 1, 1, 0, 1;"
                 : ACC8(d, 0), ACC8(d, 8), ACC8(d, 16), ACC8(d, 24), ACC8(d, 32), ACC8(d, 40), ACC8(d, 48), ACC8(d, 56)
                 : "l"(da), "l"(db));
}
template <bool ACC>
__device__ __forceinline__ void wgmma_n72_tt(float (&d)[36], uint64_t da, uint64_t db) {
    if (ACC)
        asm volatile("wgmma.mma_async.sync.aligned.m64n72k16.f32.bf16.bf16 "
                     "{%0,%1,%2,%3,%4,%5,%6,%7,%8,%9,%10,%11,%12,%13,%14,%15,%16,%17,%18,%19,%20,%21,%22,%23,%24,%25,%26,%27,%28,%29,%30,%31,"
                     "%32,%33,%34,%35}, %36, %37, 1, 1, 1, 1, 1;"
                     : ACC8(d, 0), ACC8(d, 8), ACC8(d, 16), ACC8(d, 24), "+f"(d[32]), "+f"(d[33]), "+f"(d[34]), "+f"(d[35])
                     : "l"(da), "l"(db));
    else
        asm volatile("wgmma.mma_async.sync.aligned.m64n72k16.f32.bf16.bf16 "
                     "{%0,%1,%2,%3,%4,%5,%6,%7,%8,%9,%10,%11,%12,%13,%14,%15,%16,%17,%18,%19,%20,%21,%22,%23,%24,%25,%26,%27,%28,%29,%30,%31,"
                     "%32,%33,%34,%35}, %36, %37, 0, 1, 1, 1, 1;"
                     : OUT8(d, 0), OUT8(d, 8), OUT8(d, 16), OUT8(d, 24), "=f"(d[32]), "=f"(d[33]), "=f"(d[34]), "=f"(d[35])
                     : "l"(da), "l"(db));
}
__device__ __forceinline__ void wgmma_n24_rs(float (&d)[12], const uint32_t (&a)[4], uint64_t db) {
    asm volatile("wgmma.mma_async.sync.aligned.m64n24k16.f32.bf16.bf16 "
                 "{%0,%1,%2,%3,%4,%5,%6,%7,%8,%9,%10,%11}, {%12,%13,%14,%15}, %16, 0, 1, 1, 1;"
                 : "=f"(d[0]), "=f"(d[1]), "=f"(d[2]), "=f"(d[3]), "=f"(d[4]), "=f"(d[5]), "=f"(d[6]), "=f"(d[7]),
                   "=f"(d[8]), "=f"(d[9]), "=f"(d[10]), "=f"(d[11])
                 : "r"(a[0]), "r"(a[1]), "r"(a[2]), "r"(a[3]), "l"(db));
}
template <int N> __device__ __forceinline__ void fence_regs(float (&d)[N]) {
#pragma unroll
    for (int i = 0; i < N; i++) asm volatile("" : "+f"(d[i])::"memory");
}
__device__ __forceinline__ void stsm_x4(uint32_t addr, uint32_t r0, uint32_t r1, uint32_t r2, uint32_t r3) {
    asm volatile("stmatrix.sync.aligned.m8n8.x4.shared.b16 [%0], {%1,%2,%3,%4};" ::"r"(addr), "r"(r0), "r"(r1), "r"(r2), "r"(r3) : "memory");
}
__device__ __forceinline__ uint32_t pack2(float lo, float hi) {
    uint32_t r;
    asm("cvt.rn.bf16x2.f32 %0, %1, %2;" : "=r"(r) : "f"(hi), "f"(lo));
    return r;
}
__device__ __forceinline__ float lds_f32(uint32_t addr) {
    float v;
    asm volatile("ld.shared.f32 %0, [%1];" : "=f"(v) : "r"(addr) : "memory");
    return v;
}
__device__ __forceinline__ float ex2(float x) {
    float y;
    asm("ex2.approx.ftz.f32 %0, %1;" : "=f"(y) : "f"(x));
    return y;
}
__device__ __forceinline__ float rcp(float x) {
    float y;
    asm("rcp.approx.ftz.f32 %0, %1;" : "=f"(y) : "f"(x));
    return y;
}
__device__ __forceinline__ uint32_t hmul2(uint32_t a, uint32_t b) {
    uint32_t r;
    asm("mul.rn.bf16x2 %0, %1, %2;" : "=r"(r) : "r"(a), "r"(b));
    return r;
}
__device__ __forceinline__ uint32_t phi2(float t0, float t1, float log2e = 1.4426950408889634f) {
    uint32_t e = pack2(ex2(t0 * log2e), ex2(t1 * log2e));
    uint32_t t = pack2(t0, t1), r;
    asm("min.bf16x2 %0, %0, %1;" : "+r"(e) : "r"(0x3f803f80u));
    asm("max.bf16x2 %0, %0, %1;" : "+r"(t) : "r"(0x35863586u));
    asm("add.rn.bf16x2 %0, %1, %2;" : "=r"(r) : "r"(t), "r"(e));
    return r;
}
__device__ __forceinline__ float sched_fence(uint32_t opaque) {
    float l;
    asm volatile("{\n.reg .pred p;\nmov.f32 %0, 0f3FB8AA3B;\nsetp.ne.u32 p, %1, 1;\n@p bra SF_DONE;\nSF_LOOP:\n"
                 "ld.volatile.shared.f32 %0, [%1];\nsetp.eq.f32 p, %0, 0f00000000;\n@p bra SF_LOOP;\nSF_DONE:\n}" : "=f"(l) : "r"(opaque) : "memory");
    return l;
}
__device__ __forceinline__ void sched_fence4(uint32_t opaque, uint32_t (&v)[4]) {
    asm volatile("{\n.reg .pred p;\nsetp.ne.u32 p, %4, 1;\n@p bra SF_DONE;\nSF_LOOP:\n"
                 "ld.volatile.shared.v4.u32 {%0,%1,%2,%3}, [%4];\nsetp.eq.u32 p, %0, 0;\n@p bra SF_LOOP;\nSF_DONE:\n}"
                 : "+r"(v[0]), "+r"(v[1]), "+r"(v[2]), "+r"(v[3]) : "r"(opaque) : "memory");
}
__device__ __forceinline__ bool elect_one() {
    uint32_t pred;
    asm volatile("{\n.reg .pred p;\nelect.sync _|p, 0xffffffff;\nselp.u32 %0, 1, 0, p;\n}" : "=r"(pred));
    return pred != 0;
}

struct Params {
    CUtensorMap x, qkv, wg, wu, wd, wo, out;
    const __nv_bfloat16* gate_w;
    const __nv_bfloat16* xp;
    const __nv_bfloat16* wqkv;
};

__device__ __forceinline__ int slot_block(int slot, int ct, int rank) {
    return slot == 3 ? 16 + ct : (slot == 4 ? 20 : 8 * (slot - 1)) + 2 * ct + rank;
}
__device__ __forceinline__ void slot_weights(const Params& p, int slot, int ct, int rank, const CUtensorMap*& m0,
                                             const CUtensorMap*& m1, int& c0, int& c1) {
    const int j = 2 * ct + rank;
    if (slot == 0) { m0 = m1 = &p.qkv; c0 = 512 + 64 * j; c1 = 1024 + 64 * j; }
    else if (slot == 3 && rank == 0) { m0 = m1 = &p.qkv; c0 = 128 * ct; c1 = c0 + 64; }
    else { m0 = &p.wg; m1 = &p.wu; c0 = c1 = 64 * slot_block(slot, ct, rank); }
}
constexpr int NBLK = 18;
__device__ __forceinline__ constexpr int gemm2_block(int i, int rank) {
    return i < 8 ? 2 * i + rank : i < 10 ? 16 + 2 * rank + (i - 8) : i < 12 ? 28 + 4 * rank + 2 * (i - 10)
         : i < 16 ? 20 + 2 * (i - 12) + rank : 29 + 4 * rank + 2 * (i - 16);
}
__device__ __forceinline__ int block_flag(int b) {
    return b < 16 ? 32 * (b & 1) + (b >> 1) : b < 20 ? 32 * ((b >> 1) & 1) + 8 + (b & 1) : b < 28 ? 32 * (b & 1) + (b >> 1) + 2
         : 32 * (b >> 5) + 10 + 6 * (b & 1) + ((b >> 1) & 1);
}
__device__ __forceinline__ constexpr uint32_t gstage_off(int s) { return (uint32_t)(s < 2 ? s : s == 2 ? 4 : s == 3 ? 2 : s == 4 ? 5 : 3) * 32768u; }

__device__ __forceinline__ void prefetch_slots(const Params& p, int s0, int s1, int ct, int rank, int rb) {
    for (int slot = s0; slot < s1; slot++) {
        const CUtensorMap *m0, *m1; int c0, c1;
        slot_weights(p, slot, ct, rank, m0, m1, c0, c1);
        tma_prefetch_2d((rb & 1) ? m1 : m0, (rb & 1) ? c1 : c0, 64 * (rb >> 1));
    }
}
__device__ __forceinline__ void prefetch_phase2(const Params& p, int ct, int rank, int rb) {
    for (int i = rb; i < NBLK; i += 16) {
        const int blk = gemm2_block(i, rank);
        if (blk < 28) tma_prefetch_3d(&p.wd, 0, 64 * blk, 2 * ct);
        else tma_prefetch_3d(&p.wo, 0, 64 * (blk - 28), 2 * ct);
    }
    prefetch_tmap(&p.out);
}
__device__ __forceinline__ uint32_t stale_sectors(const uint32_t (&o)[4], uint32_t off, uint32_t want) {
    uint32_t v[16], b0 = 0, b1 = 0;
#pragma unroll
    for (int k = 0; k < 16; k++) asm volatile("ld.shared.u32 %0, [%1];" : "=r"(v[k]) : "r"(o[k & 3] + off + (k >> 2) * 4096) : "memory");
#pragma unroll
    for (int k = 0; k < 16; k += 2) {
        asm("lop3.b32 %0, %0, %1, %2, 0xF6;" : "+r"(b0) : "r"(v[k]), "r"(want));
        asm("lop3.b32 %0, %0, %1, %2, 0xF6;" : "+r"(b1) : "r"(v[k + 1]), "r"(want));
    }
    return b0 | b1;
}
__device__ __forceinline__ void tag_addresses(uint32_t (&o)[4], uint32_t sb, uint32_t lane) {
#pragma unroll
    for (int t = 0; t < 4; t++) o[t] = sb + lane * 128 + ((lane >> 3) << 2) + (((2 * t) ^ (lane & 7)) << 4);
}
__device__ __noinline__ uint32_t reload_block(uint32_t sb, uint32_t off, uint32_t want, const uint8_t* src, uint32_t rph) {
    uint32_t o[4];
    tag_addresses(o, sb, threadIdx.x & 31);
    for (uint32_t n = 0;; n++) {
        if ((threadIdx.x & 31) == 0) {
            mbar_expect_tx(sb + RETRY, BLK);
            bulk_load(sb + off, src, BLK, sb + RETRY);
        }
        mbar_wait(sb + RETRY, rph);
        rph ^= 1;
        if (!__any_sync(0xffffffffu, stale_sectors(o, off, want) & 1)) return rph;
        if (n > 100000) __trap();
    }
}
template <bool LAST>
__device__ __forceinline__ uint32_t tile_mainloop(float (&acc)[2][64], uint32_t sb, int slot, int wg, int lane) {
    const uint64_t da0 = desc_a(sb + OFF_X), db0 = desc_b(sb + OFF_B);
    uint32_t s = (slot * 8) % NSLOT, ph = ((slot * 8) / NSLOT) & 1, prev = 0;
    if (!LAST && slot == 0) mbar_wait(sb + XFULL, 0);
    mbar_wait(sb + BFULL + 8 * s, ph);
#pragma unroll
    for (int kb = 0; kb < 8; kb++) {
        const uint64_t da = da0 + kb * 1024, db = db0 + s * 1024;
        if (kb == 7 && !LAST && slot != 0) bar_arrive(wg == 0 ? BAR_ORDER1 : BAR_ORDER0, 256);
        wgmma_fence();
        if (kb == 0) {
            wgmma_n128_first(acc[0], da, db); wgmma_n128_first(acc[1], da + 512, db);
            wgmma_n128(acc[0], da + 2, db + 128); wgmma_n128(acc[1], da + 514, db + 128);
        } else if (kb < 7) {
            wgmma_n128(acc[0], da, db); wgmma_n128(acc[1], da + 512, db);
            wgmma_n128(acc[0], da + 2, db + 128); wgmma_n128(acc[1], da + 514, db + 128);
        } else {
            wgmma_n128(acc[0], da, db); wgmma_n128(acc[0], da + 2, db + 128);
            wgmma_n128(acc[0], da + 4, db + 256); wgmma_n128(acc[0], da + 6, db + 384);
        }
        wgmma_commit();
        if (kb > 0) {
            wgmma_wait<1>();
            if (lane == 0) {
                mbar_arrive(sb + BEMPTY + 8 * prev);
                if (LAST) {
                    if (kb == 2) mbar_arrive(sb + GEMPTY + 0);
                    if (kb >= 4) mbar_arrive(sb + GEMPTY + 8 * (kb - 3));
                }
            }
        }
        prev = s;
        if (++s == NSLOT) { s = 0; ph ^= 1; }
        if (kb < 7) {
            wgmma_fence();
            wgmma_n128(acc[0], da + 4, db + 256);
            wgmma_n128(acc[1], da + 516, db + 256);
            wgmma_commit();
            if (!LAST && slot == 0) mbar_wait(sb + XFULL + 8 * (kb + 1), 0);
            mbar_wait(sb + BFULL + 8 * s, ph);
            wgmma_fence();
            wgmma_n128(acc[0], da + 6, db + 384);
            wgmma_n128(acc[1], da + 518, db + 384);
            wgmma_commit();
        } else {
            wgmma_fence();
            wgmma_n128(acc[1], da + 512, db); wgmma_n128(acc[1], da + 514, db + 128);
            if (!LAST) { wgmma_commit(); if (slot == 0) bar_arrive(BAR_ORDER1, 256); wgmma_fence(); }
            wgmma_n128(acc[1], da + 516, db + 256); wgmma_n128(acc[1], da + 518, db + 384);
            wgmma_commit();
        }
    }
    return prev;
}

__global__ void __cluster_dims__(2, 1, 1) __launch_bounds__(384, 1)
fused_kernel(const __grid_constant__ Params p) {
    extern __shared__ __align__(1024) uint8_t smem_raw[];
    if (threadIdx.x == 256) { prefetch_tmap(&p.x); prefetch_tmap(&p.qkv); }
    const uint32_t sb = __shfl_sync(0xffffffffu, smem_u32(smem_raw), 0);
    const int warp = __shfl_sync(0xffffffffu, threadIdx.x >> 5, 0), lane = threadIdx.x & 31;
    const int rank = blockIdx.x & 1;
    int rb, ct;
    {
        const int c = blockIdx.x >> 1;
        if (c < 4) { rb = 15; ct = c; }
        else if (c < 36) { rb = (c - 4) & 7; ct = (c - 4) >> 3; }
        else { rb = 8 + (c - 36) % 7; ct = (c - 36) / 7; }
    }
    const int j = 2 * ct + rank;

    if (warp == 0 && lane < 24) {
        const __nv_bfloat16* a = lane < 16 ? p.xp + (size_t)(128 * rb + 16 * j + lane) * DM
                                           : p.wqkv + (size_t)(4 * rb + (lane & 3)) * (3 * DM) + 512 + 128 * (lane & 4) + 64 * j;
        asm volatile("prefetch.global.L2 [%0];" ::"l"(a) : "memory");
    }
    if (warp == 8 && elect_one()) {
        for (int i = 0; i < 13; i++) mbar_init(sb + XFULL + 8 * i, 1);
        asm volatile("fence.proxy.async.shared::cta;" ::: "memory");
        mbar_expect_tx(sb + XFULL, BLK);
        tma_load_2d(sb + OFF_X, &p.x, 0, 128 * rb, sb + XFULL);
        mbar_expect_tx(sb + BFULL, BLK);
        tma_load_2d(sb + OFF_B, &p.qkv, 512 + 64 * j, 0, sb + BFULL);
        tma_load_2d(sb + OFF_B + 8192, &p.qkv, 1024 + 64 * j, 0, sb + BFULL);
    } else if (warp == 9 && elect_one()) {
        if (sb & 1023) __trap();
        for (int i = 0; i < NSLOT; i++) mbar_init(sb + BEMPTY + 8 * i, 4);
        for (int i = 0; i < 6; i++) { mbar_init(sb + GFULL + 8 * i, 2); mbar_init(sb + GEMPTY + 8 * i, 8); }
        mbar_init(sb + GREADY, 2); mbar_init(sb + EREADY, 1);
        for (int i = 0; i < 3; i++) mbar_init(sb + STGFREE + 8 * i, 1);
        for (int i = 0; i < 7; i++) mbar_init(sb + GOK + 8 * i, 1);
        mbar_init(sb + H4RDY, 4); mbar_init(sb + KVREADY, 2); mbar_init(sb + TXOK, 1);
        for (int i = 0; i < 4; i++) { mbar_init(sb + RXFULL + 8 * i, 1); mbar_expect_tx(sb + RXFULL + 8 * i, 4096); }
        asm volatile("st.shared.u32 [%0], %1;" ::"r"(sb + OFF_EPOCH + 4), "r"(0u) : "memory");
        asm volatile("fence.mbarrier_init.release.cluster;" ::: "memory");
    }
    __syncthreads();
    asm volatile("barrier.cluster.arrive.relaxed.aligned;" ::: "memory");

    if (warp >= 8) {
        asm volatile("setmaxnreg.dec.sync.aligned.u32 40;");
        if (warp == 8) {
            if (elect_one()) {
#pragma unroll
                for (int k = 1; k < 8; k++) {
                    if (k >= NSLOT) mbar_wait(sb + BEMPTY + 8 * (k - NSLOT), 0);
                    else if (k >= 3) mbar_wait(sb + BFULL + 8 * (k - 3), 0);
                    const uint32_t s = k % NSLOT;
                    mbar_expect_tx(sb + XFULL + 8 * k, BLK);
                    tma_load_2d(sb + OFF_X + k * BLK, &p.x, 64 * k, 128 * rb, sb + XFULL + 8 * k);
                    mbar_expect_tx(sb + BFULL + 8 * s, BLK);
                    tma_load_2d(sb + OFF_B + s * BLK, &p.qkv, 512 + 64 * j, 64 * k, sb + BFULL + 8 * s);
                    tma_load_2d(sb + OFF_B + s * BLK + 8192, &p.qkv, 1024 + 64 * j, 64 * k, sb + BFULL + 8 * s);
                }
                uint32_t s = 3, ph = 0;
#pragma unroll 1
                for (int slot = 1; slot < 5; slot++) {
                    const CUtensorMap *m0, *m1; int c0, c1;
                    slot_weights(p, slot, ct, rank, m0, m1, c0, c1);
#pragma unroll 1
                    for (int kb = 0; kb < 8; kb++) {
                        mbar_wait(sb + BEMPTY + 8 * s, ph);
                        mbar_expect_tx(sb + BFULL + 8 * s, BLK);
                        tma_load_2d(sb + OFF_B + s * BLK, m0, c0, 64 * kb, sb + BFULL + 8 * s);
                        tma_load_2d(sb + OFF_B + s * BLK + 8192, m1, c1, 64 * kb, sb + BFULL + 8 * s);
                        if (++s == NSLOT) { s = 0; ph ^= 1; }
                    }
                }
#pragma unroll
                for (int i = 0; i < NBLK; i++) {
                    const int s = i % 6, blk = gemm2_block(i, rank);
                    mbar_wait(sb + GEMPTY + 8 * s, (i / 6) & 1);
                    mbar_expect_tx(sb + GFULL + 8 * s, BLK);
                    tma_load_3d(sb + gstage_off(s) + BLK, blk < 28 ? &p.wd : &p.wo, 0, 64 * (blk < 28 ? blk : blk - 28), 2 * ct, sb + GFULL + 8 * s);
                }
            }
        } else if (warp == 9) {
            if (elect_one()) {
                asm volatile("st.shared.u32 [%0], %1;" ::"r"(sb + OFF_EPOCH), "r"(ld_relaxed(g_kvcnt + 32 * j) >> 4) : "memory");
                mbar_arrive(sb + EREADY);
                mbar_wait(sb + XFULL, 0);
                if (rb < 6) tma_prefetch_2d(&p.qkv, 512 + 512 * (rb & 1) + 64 * j, 320 + 64 * (rb >> 1));
                mbar_wait(sb + XFULL + 16, 0);
                prefetch_slots(p, 1, 2, ct, rank, rb);
                mbar_wait(sb + XFULL + 56, 0);
                prefetch_slots(p, 2, 5, ct, rank, rb);
                prefetch_phase2(p, ct, rank, rb);
            }
            __syncwarp();
            uint32_t epoch;
            asm volatile("ld.shared.u32 %0, [%1];" : "=r"(epoch) : "r"(sb + OFF_EPOCH) : "memory");
            if (lane < 17) reinterpret_cast<float4*>(&g_kvacc[(epoch + 1) & 1][0][0])[blockIdx.x * 17 + lane] = make_float4(0.f, 0.f, 0.f, 0.f);
#pragma unroll 1
            for (int u = 0; u < 3 + rank; u++) {
                bar_sync(BAR_STORE, 160);
                if (elect_one()) {
                    if (u == 0) {
                        mbar_arrive(sb + STGFREE);
                        asm volatile("fence.acq_rel.gpu;" ::: "memory");
                        asm volatile("red.relaxed.gpu.global.add.u32 [%0], %1;" ::"l"(g_kvcnt + 32 * j), "r"(1u) : "memory");
                    } else {
                        const int blk = slot_block(u, ct, rank);
                        bulk_store(g_hbuf + (size_t)(rb * NKB2 + blk) * BLK, sb + OFF_STG, BLK);
                        asm volatile("cp.async.bulk.commit_group;" ::: "memory");
                        asm volatile("cp.async.bulk.wait_group.read 0;" ::: "memory");
                        if (u < 3) mbar_arrive(sb + STGFREE + 8 * u);
                        st_relaxed(g_flags + rb * 64 + block_flag(blk), epoch + 1);
                    }
                }
                __syncwarp();
            }
            {
                const uint32_t want = epoch + 1;
                uint32_t o[4], rph = 0;
                tag_addresses(o, sb, lane);
#pragma unroll 1
                for (int r = 0; r < NBLK / 6; r++) {
#pragma unroll
                    for (int s = 0; s < 6; s++) {
                        mbar_wait(sb + GFULL + 8 * s, r & 1);
                        if (__any_sync(0xffffffffu, stale_sectors(o, gstage_off(s), want) & 1))
                            rph = reload_block(sb, gstage_off(s), want, g_hbuf + (size_t)(rb * NKB2 + gemm2_block(6 * r + s, rank)) * BLK, rph);
                        if (lane == 0) mbar_arrive(sb + GOK + 8 * s);
                    }
                }
            }
        } else {
            const int gk = lane >> 2, cA = 2 * (lane & 3) + (gk & 1), cB = cA ^ 1;
            const uint4 wa = *reinterpret_cast<const uint4*>(p.gate_w + 64 * gk + 8 * cA);
            const uint4 wb = *reinterpret_cast<const uint4*>(p.gate_w + 64 * gk + 8 * cB);
            const uint32_t ww[8] = {wa.x, wa.y, wa.z, wa.w, wb.x, wb.y, wb.z, wb.w};
            mbar_wait(sb + EREADY, 0);
            uint32_t epoch;
            asm volatile("ld.shared.u32 %0, [%1];" : "=r"(epoch) : "r"(sb + OFF_EPOCH) : "memory");
#pragma unroll 1
            for (int k = 0; k < 8; k++) mbar_wait(sb + XFULL + 8 * k, 0);
            float mine = 0.f;
            const uint32_t row0 = 16 * j + 8 * (warp - 10);
#pragma unroll 1
            for (uint32_t rq = 0; rq < 8; rq += 2) {
                uint32_t v[2][8];
#pragma unroll
                for (int r = 0; r < 2; r++) {
                    const uint32_t a = sb + OFF_X + gk * BLK + (row0 + rq + r) * 128;
                    asm volatile("ld.shared.v4.u32 {%0,%1,%2,%3}, [%4];" : "=r"(v[r][0]), "=r"(v[r][1]), "=r"(v[r][2]), "=r"(v[r][3])
                                 : "r"(a + ((cA ^ (rq + r)) << 4)) : "memory");
                    asm volatile("ld.shared.v4.u32 {%0,%1,%2,%3}, [%4];" : "=r"(v[r][4]), "=r"(v[r][5]), "=r"(v[r][6]), "=r"(v[r][7])
                                 : "r"(a + ((cB ^ (rq + r)) << 4)) : "memory");
                }
                float s[2];
#pragma unroll
                for (int r = 0; r < 2; r++) {
                    float s0 = 0.f, s1 = 0.f;
#pragma unroll
                    for (int i = 0; i < 8; i++) {
                        s0 = fmaf(__uint_as_float(v[r][i] << 16), __uint_as_float(ww[i] << 16), s0);
                        s1 = fmaf(__uint_as_float(v[r][i] & 0xffff0000u), __uint_as_float(ww[i] & 0xffff0000u), s1);
                    }
                    s[r] = s0 + s1;
                }
                float t = (lane & 16) ? s[1] : s[0];
                t += __shfl_xor_sync(0xffffffffu, (lane & 16) ? s[0] : s[1], 16);
#pragma unroll
                for (int o = 8; o > 0; o >>= 1) t += __shfl_xor_sync(0xffffffffu, t, o);
                if ((lane & 15) == rq) mine = t;
            }
            if ((lane & 9) == 0) {
                const float g = ex2(-1.4426950408889634f * mine);
                const unsigned long long e = ((unsigned long long)(epoch + 1) << 32) | __float_as_uint(g);
                asm volatile("st.relaxed.gpu.global.u64 [%0], %1;" ::"l"(g_gate + 128 * rb + row0 + (lane & 7) + (lane >> 4)), "l"(e) : "memory");
            }
            {
                const int r = 64 * (warp - 10) + lane;
                unsigned long long e0, e1;
                uint32_t n = 0;
                do {
                    asm volatile("ld.relaxed.gpu.global.u64 %0, [%1];" : "=l"(e0) : "l"(g_gate + 128 * rb + r) : "memory");
                    asm volatile("ld.relaxed.gpu.global.u64 %0, [%1];" : "=l"(e1) : "l"(g_gate + 128 * rb + r + 32) : "memory");
                    if (++n > SPIN_LIMIT) __trap();
                } while (!__all_sync(0xffffffffu, (uint32_t)(e0 >> 32) == epoch + 1 && (uint32_t)(e1 >> 32) == epoch + 1));
                asm volatile("st.shared.u32 [%0], %1;" ::"r"(sb + OFF_G + 4 * r), "r"((uint32_t)e0) : "memory");
                asm volatile("st.shared.u32 [%0], %1;" ::"r"(sb + OFF_G + 4 * r + 128), "r"((uint32_t)e1) : "memory");
                __syncwarp();
                if (lane == 0) { mbar_arrive(sb + GREADY); }
            }
            if (rank == 0) {
                const int h0 = 4 * (warp - 10);
                wait_count(g_kvcnt + 32 * (j + warp - 10), (epoch + 1) << 4);
                const float* src = &g_kvacc[epoch & 1][8 * ct + h0][0];
                uint32_t f[4][6];
#pragma unroll
                for (int h = 0; h < 4; h++) {
                    const float4 u0 = ld_cg4(src + h * 272 + lane * 8), u1 = ld_cg4(src + h * 272 + lane * 8 + 4);
                    const float za = __uint_as_float(ld_relaxed(reinterpret_cast<const uint32_t*>(src + h * 272 + 256 + (lane >> 2))));
                    const float zb = __uint_as_float(ld_relaxed(reinterpret_cast<const uint32_t*>(src + h * 272 + 264 + (lane >> 2))));
                    f[h][0] = pack2(u0.x, u0.y); f[h][1] = pack2(u0.z, u0.w); f[h][2] = pack2(u1.x, u1.y);
                    f[h][3] = pack2(u1.z, u1.w); f[h][4] = pack2(za, za); f[h][5] = pack2(zb, zb);
                }
                mbar_wait(sb + STGFREE + 16, 0);
#pragma unroll
                for (int h = 0; h < 4; h++)
#pragma unroll
                    for (int i = 0; i < 6; i++)
                        asm volatile("st.shared.u32 [%0], %1;" ::"r"(sb + OFF_STG + 8192 + (h0 + h) * 768 + i * 128 + lane * 4), "r"(f[h][i]) : "memory");
                asm volatile("fence.proxy.async.shared::cta;" ::: "memory");
                __syncwarp();
                if (lane == 0) { mbar_arrive(sb + KVREADY); }
            }
            if (warp == 11) {
                const uint32_t* fl = g_flags + rb * 64 + rank * 32 + lane;
                const uint32_t full = (1u << NBLK) - 1;
                uint32_t ready = 0, n = 0;
                while (ready != full) {
                    const uint32_t v = lane < NBLK ? ld_acquire(fl) : 0;
                    const uint32_t now = __ballot_sync(0xffffffffu, v == epoch + 1) & full;
                    if (now != ready) {
                        ready = now;
                        __syncwarp();
                        if (lane == 0) asm volatile("st.release.cta.shared.u32 [%0], %1;" ::"r"(sb + OFF_EPOCH + 4), "r"(__ffs(~now) - 1) : "memory");
                    } else {
                        __nanosleep(100);
                    }
                    if (++n > SPIN_LIMIT) __trap();
                }
            } else {
                asm volatile("barrier.cluster.wait.aligned;" ::: "memory");
                if (elect_one()) {
                    const uint8_t* hb = g_hbuf + (size_t)rb * NKB2 * BLK;
                    uint32_t have = 0;
#pragma unroll
                    for (int i = 0; i < NBLK; i++) {
                        const int s = i % 6;
                        mbar_wait(sb + GEMPTY + 8 * s, (i / 6) & 1);
                        uint32_t n = 0;
                        while (have <= i) {
                            if (n) __nanosleep(40);
                            asm volatile("ld.acquire.cta.shared.u32 %0, [%1];" : "=r"(have) : "r"(sb + OFF_EPOCH + 4) : "memory");
                            if (++n > (SPIN_LIMIT << 2)) __trap();
                        }
                        asm volatile("fence.proxy.async.global;" ::: "memory");
                        mbar_expect_tx(sb + GFULL + 8 * s, BLK);
                        bulk_load(sb + gstage_off(s), hb + (size_t)gemm2_block(i, rank) * BLK, BLK, sb + GFULL + 8 * s);
                        if (i == 7) {
                            const int blk = slot_block(4, ct, rank);
                            mbar_wait(sb + H4RDY, 0);
                            bulk_store(g_hbuf + (size_t)(rb * NKB2 + blk) * BLK, sb + OFF_RX, BLK);
                            asm volatile("cp.async.bulk.commit_group;" ::: "memory");
                            st_relaxed(g_flags + rb * 64 + block_flag(blk), epoch + 1);
                        } else if (i == 9) {
                            asm volatile("cp.async.bulk.wait_group.read 0;" ::: "memory");
                            mbar_arrive_remote(mapa(sb + TXOK, rank ^ 1));
                        }
                    }
                }
            }
        }
    } else {
        asm volatile("setmaxnreg.inc.sync.aligned.u32 232;");
        const int wg = warp >> 2, w = warp & 3;
        const uint32_t stg = sb + OFF_STG;
        const uint32_t st_row = (uint32_t)(16 * w + (lane & 15)) * 128;
        const uint32_t st_sw = lane & 7, st_hi = lane >> 4;
        const int grow = 16 * w + (lane >> 2);

        const uint32_t ta0 = ~(uint32_t)((lane & 3) == ((2 * w) & 3)), ta1 = ~(uint32_t)((lane & 3) == ((2 * w + 1) & 3));
        uint32_t epoch1 = 0, to0 = 0, to1 = 0;
#define TAG0(x) (((x) & ta0) | to0)
#define TAG1(x) (((x) & ta1) | to1)
        uint32_t sc[4];
        for (int slot = wg; slot < 4; slot += 2) {
            float acc[2][64];
            if (slot > 0) bar_sync(wg == 0 ? BAR_ORDER0 : BAR_ORDER1, 256);
            const uint32_t prev = tile_mainloop<false>(acc, sb, slot, wg, lane);
            wgmma_wait<0>();
            fence_regs(acc[0]); fence_regs(acc[1]);
            if (lane == 0) {
                mbar_arrive(sb + BEMPTY + 8 * prev);
                if (slot == 3) for (int i = 0; i < 6; i++) mbar_arrive(sb + GEMPTY + 8 * i);
            }
            if (slot < 2) {
                mbar_wait(sb + EREADY, 0);
                asm volatile("ld.shared.u32 %0, [%1];" : "=r"(epoch1) : "r"(sb + OFF_EPOCH) : "memory");
                epoch1++;
                to0 = ~ta0 & epoch1; to1 = ~ta1 & epoch1;
            }

            if (slot == 0) {
                float d[36];
                asm volatile("st.shared.v4.u32 [%0], {%1,%1,%1,%1};" ::"r"(sb + OFF_ONES + threadIdx.x * 16), "r"(0x3f803f80u) : "memory");
#define STS_V(b, jp) stsm_x4(stg + 8192 + st_row + (((2 * (jp) + st_hi) ^ st_sw) << 4), pack2(acc[b][32 + 8 * (jp)], acc[b][33 + 8 * (jp)]), \
                             pack2(acc[b][34 + 8 * (jp)], acc[b][35 + 8 * (jp)]), pack2(acc[b][36 + 8 * (jp)], acc[b][37 + 8 * (jp)]),      \
                             pack2(acc[b][38 + 8 * (jp)], acc[b][39 + 8 * (jp)]))
#define PHI_K(r, b, jp) _Pragma("unroll") for (int i = 0; i < 4; i++) r[i] = phi2(acc[b][8 * (jp) + 2 * i], acc[b][8 * (jp) + 2 * i + 1], l2e)
#define STS_K(r, jp) stsm_x4(stg + st_row + (((2 * (jp) + st_hi) ^ st_sw) << 4), r[0], r[1], r[2], r[3])
#define KV_MMA(b)                                                                                        \
    asm volatile("fence.proxy.async.shared::cta;" ::: "memory");                                         \
    bar_sync(BAR_WG0, 128);                                                                              \
    wgmma_fence();                                                                                       \
    _Pragma("unroll") for (int t = 0; t < 4; t++) {                                                      \
        const uint64_t db = desc_b(stg + 8192 + t * 2048, OFF_ONES - OFF_STG - 8192 - t * 2048);         \
        if (b == 0 && t == 0) wgmma_n72_tt<false>(d, desc_b(stg + t * 2048), db);                        \
        else wgmma_n72_tt<true>(d, desc_b(stg + t * 2048), db);                                          \
    }                                                                                                    \
    wgmma_commit();
                uint32_t k0[4], k1[4], k2[4], k3[4];
                STS_V(0, 0); STS_V(0, 1); STS_V(0, 2); STS_V(0, 3);
                float l2e = sched_fence(sb);
                PHI_K(k0, 0, 0); PHI_K(k1, 0, 1); STS_K(k0, 0); STS_K(k1, 1);
                l2e = sched_fence(sb);
                PHI_K(k2, 0, 2); STS_K(k2, 2);
                l2e = sched_fence(sb);
                PHI_K(k3, 0, 3); STS_K(k3, 3);
                KV_MMA(0)
                PHI_K(k0, 1, 0); PHI_K(k1, 1, 1);
                wgmma_wait<0>();
                bar_sync(BAR_WG0, 128);
                STS_K(k0, 0); STS_K(k1, 1);
                STS_V(1, 0); STS_V(1, 1); STS_V(1, 2); STS_V(1, 3);
                l2e = sched_fence(sb);
                PHI_K(k2, 1, 2); PHI_K(k3, 1, 3); STS_K(k2, 2); STS_K(k3, 3);
                KV_MMA(1)
#undef STS_V
#undef PHI_K
#undef STS_K
#undef KV_MMA
                float* dst = &g_kvacc[(epoch1 - 1) & 1][4 * j + w][0];
                wgmma_wait<0>();
                fence_regs(d);
                float c[8];
#pragma unroll
                for (int i = 0; i < 8; i++) c[i] = w == 0 ? d[i] : w == 1 ? d[8 + i] : w == 2 ? d[16 + i] : d[24 + i];
                red_add_v4(dst + lane * 8, c[0], c[1], c[2], c[3]);
                red_add_v4(dst + lane * 8 + 4, c[4], c[5], c[6], c[7]);
                if ((lane & 3) < 2)
                    asm volatile("red.relaxed.gpu.global.add.f32 [%0], %1;" ::"l"(dst + 256 + (lane >> 2) + 8 * (lane & 1)), "f"((lane & 1) ? d[34] : d[32]) : "memory");
            } else if (slot == 3 && rank == 0) {
                constexpr int QG = 2, NS = 16 / QG, SPQ = 4 / QG;
                uint32_t a[2][QG][4];
#define PACK_Q(buf, step)                                                                                     \
    _Pragma("unroll") for (int u = 0; u < QG; u++) {                                                          \
        const float* q = &acc[((step) / SPQ) & 1][32 * ((step) / (2 * SPQ)) + 8 * (QG * ((step) % SPQ) + u)]; \
        _Pragma("unroll") for (int i = 0; i < 4; i++) a[buf][u][i] = phi2(q[2 * i], q[2 * i + 1]);            \
    }
                PACK_Q(0, 0)
                mbar_wait(sb + KVREADY, 0);
                float g[4], ge[4];
#pragma unroll
                for (int i = 0; i < 4; i++) {
                    g[i] = 1.f + lds_f32(sb + OFF_G + 4 * (64 * (i >> 1) + grow + 8 * (i & 1)));
                    ge[i] = g[i] * 1e-6f;
                }
                const uint64_t dkv = (uint64_t)((((stg + 8192) & 0x3FFFF) >> 4) | (8u << 16)) | ((uint64_t)16u << 32);
                uint8_t* const odst = g_hbuf + (size_t)(rb * NKB2 + 28 + 2 * ct) * BLK;
#pragma unroll
                for (int step = 0; step < NS; step++) {
                    const int qt = step / SPQ, b = qt & 1, h0 = 4 * (qt >> 1) + QG * (step % SPQ);
                    float d[QG][12];
                    wgmma_fence();
#pragma unroll
                    for (int u = 0; u < QG; u++) wgmma_n24_rs(d[u], a[step & 1][u], dkv + 48 * (h0 + u));
                    wgmma_commit();
                    if (step + 1 < NS) { PACK_Q((step + 1) & 1, step + 1) }
                    wgmma_wait<0>();
                    if (step > 0 && step % SPQ == 0) {
                        if (threadIdx.x == 128) asm volatile("cp.async.bulk.wait_group.read 0;" ::: "memory");
                        bar_sync(BAR_WG1, 128);
                    }
#pragma unroll
                    for (int u = 0; u < QG; u++) {
                        fence_regs(d[u]);
                        const float r0 = rcp(fmaf(d[u][8], g[2 * b], ge[2 * b])), r1 = rcp(fmaf(d[u][10], g[2 * b + 1], ge[2 * b + 1]));
                        stsm_x4(stg + st_row + (((2 * ((h0 + u) & 3) + st_hi) ^ st_sw) << 4),
                                TAG0(pack2(d[u][0] * r0, d[u][1] * r0)), TAG1(pack2(d[u][2] * r1, d[u][3] * r1)),
                                pack2(d[u][4] * r0, d[u][5] * r0), pack2(d[u][6] * r1, d[u][7] * r1));
                    }
                    if (step % SPQ == SPQ - 1) {
                        asm volatile("fence.proxy.async.shared::cta;" ::: "memory");
                        bar_sync(BAR_WG1, 128);
                        if (threadIdx.x == 128) {
                            bulk_store(odst + qt * 8192, stg, 8192);
                            asm volatile("cp.async.bulk.commit_group;" ::: "memory");
                            if (qt & 1) st_relaxed(g_flags + rb * 64 + block_flag(28 + 2 * ct + (qt >> 1)), epoch1);
                            if (qt == 3) asm volatile("cp.async.bulk.wait_group.read 0;" ::: "memory");
                        }
                        __syncwarp();
                    }
                }
#undef PACK_Q
                break;
            } else {
                uint32_t pg[2][32];
#pragma unroll
                for (int b = 0; b < 2; b++)
#pragma unroll
                    for (int i = 0; i < 32; i++) pg[b][i] = pack2(acc[b][2 * i], acc[b][2 * i + 1]);
                if (slot < 3) {
                    mbar_wait(sb + GREADY, 0);
#pragma unroll
                    for (int i = 0; i < 4; i++) {
                        const float f = 1.f - rcp(1.f + lds_f32(sb + OFF_G + 4 * (64 * (i >> 1) + grow + 8 * (i & 1))));
                        sc[i] = pack2(f, f);
                    }
                }
                mbar_wait(sb + STGFREE + 8 * (slot - 1), 0);
                sched_fence4(sb, sc);
#pragma unroll
                for (int b = 0; b < 2; b++) {
#pragma unroll
                    for (int jp = 0; jp < 4; jp++) {
                        const uint32_t* g = &pg[b][4 * jp];
                        stsm_x4(stg + b * 8192 + st_row + (((2 * jp + st_hi) ^ st_sw) << 4),
                                TAG0(hmul2(hmul2(g[0], sc[2 * b]), g[16])), TAG1(hmul2(hmul2(g[1], sc[2 * b + 1]), g[17])),
                                hmul2(hmul2(g[2], sc[2 * b]), g[18]), hmul2(hmul2(g[3], sc[2 * b + 1]), g[19]));
                    }
                }
                asm volatile("fence.proxy.async.shared::cta;" ::: "memory");
            }
            bar_arrive(BAR_STORE, 160);
        }

        if (wg == 0) {
            float acc[2][64];
            float (&accS)[64] = acc[0];
            float (&accK)[64] = acc[1];
            asm volatile("barrier.cluster.wait.aligned;" ::: "memory");
            bar_sync(BAR_ORDER0, 256);
            tile_mainloop<true>(acc, __shfl_sync(0xffffffffu, sb, 0), 4, 0, lane);
            const uint64_t dS = desc_a(sb + (rank ^ 1) * 8192), dK = desc_a(sb + rank * 8192), dB = desc_b(sb + BLK);
            uint32_t s = 1, ph = 0;
            int64_t off = 2048;
            uint32_t h[2][16];
#define PACK_H(b)                                                                                             \
    _Pragma("unroll") for (int i = 0; i < 16; i++)                                                            \
        h[b][i] = hmul2(pack2(acc[b][2 * i] * acc[b][32 + 2 * i], acc[b][2 * i + 1] * acc[b][33 + 2 * i]), sc[2 * (b) + (i & 1)]);
#define STS_H(t) stsm_x4(sb + OFF_RX + ((t) >> 2) * 8192 + st_row + (((2 * ((t) & 3) + st_hi) ^ st_sw) << 4), TAG0(h[(t) >> 2][4 * ((t) & 3)]), \
                         TAG1(h[(t) >> 2][4 * ((t) & 3) + 1]), h[(t) >> 2][4 * ((t) & 3) + 2], h[(t) >> 2][4 * ((t) & 3) + 3])
            mbar_wait(sb + GOK, 0);
            wgmma_wait<1>();
            fence_regs(acc[0]);
            PACK_H(0)
            wgmma_fence();
            wgmma_n128_restart(accS, dS, dB);
            wgmma_n128(accS, dS + 2, dB + 128);
            wgmma_n128(accS, dS + 4, dB + 256);
            wgmma_n128(accS, dS + 6, dB + 384);
            wgmma_commit();
            wgmma_wait<1>();
            fence_regs(acc[1]);
            if (lane == 0) mbar_arrive(sb + GEMPTY + 40);
            PACK_H(1)
            wgmma_fence();
            wgmma_n128_restart(accK, dK, dB);
            wgmma_commit();
            bar_sync(BAR_WG0, 128);
#pragma unroll
            for (int k = 1; k < 4; k++) {
                STS_H(k - 1);
                if (k == 3) mbar_wait(sb + GOK + 8, 0);
                wgmma_fence();
                wgmma_n128(accK, dK + 2 * k, dB + 128 * k);
                wgmma_commit();
            }
#define G2_NEXT() do { off += s == 0 ? 2048 : s == 5 ? -6144 : (s & 1) ? 6144 : -4096; if (++s == 6) { s = 0; ph ^= 1; } } while (0)
#define G2_BLOCK(A, B, C)                                                                                     \
    {                                                                                                         \
        const uint64_t aS = dS + off, aK = dK + off, db = dB + off;                                           \
        wgmma_fence();                                                                                        \
        wgmma_n128(accS, aS, db);                                                                             \
        wgmma_n128(accK, aK, db);                                                                             \
        wgmma_n128(accS, aS + 2, db + 128);                                                                   \
        wgmma_n128(accK, aK + 2, db + 128);                                                                   \
        wgmma_commit();                                                                                       \
        wgmma_wait<1>();                                                                 \
        if (lane == 0) mbar_arrive2(sb + GEMPTY + 8 * (s == 0 ? 5 : s - 1));                                  \
        A;                                                                                                    \
        wgmma_fence();                                                                                        \
        wgmma_n128(accS, aS + 4, db + 256);                                                                   \
        wgmma_n128(accK, aK + 4, db + 256);                                                                   \
        wgmma_commit();                                                                                       \
        B;                                                                                                    \
        G2_NEXT();                                                                                            \
        mbar_wait(sb + GOK + 8 * s, ph);                                                                    \
        wgmma_fence();                                                                                        \
        wgmma_n128(accS, aS + 6, db + 384);                                                                   \
        wgmma_n128(accK, aK + 6, db + 384);                                                                   \
        wgmma_commit();                                                                                       \
        C;                                                                                                    \
    }
            G2_BLOCK({ STS_H(3); STS_H(4); }, STS_H(5), { STS_H(6); STS_H(7); })
#pragma unroll 1
            for (int i = 2; i < NBLK - TAIL_LEAD; i++) {
                G2_BLOCK(, if (i == 2) {
                    asm volatile("fence.proxy.async.shared::cta;" ::: "memory");
                    __syncwarp();
                    if (lane == 0) mbar_arrive(sb + H4RDY);
                }, )
            }
#undef PACK_H
#undef STS_H
#undef G2_BLOCK
            int64_t offs[TAIL_LEAD];
#pragma unroll
            for (int t = 0; t < TAIL_LEAD; t++) {
                offs[t] = off;
                wgmma_fence();
                wgmma_n128(accS, dS + off, dB + off);
                wgmma_n128(accS, dS + off + 2, dB + off + 128);
                wgmma_commit();
                if (t == 0) {
                    wgmma_wait<1>();
                    if (lane == 0) mbar_arrive2(sb + GEMPTY + 8 * (s == 0 ? 5 : s - 1));
                }
                const int64_t cur = off;
                wgmma_fence();
                wgmma_n128(accS, dS + cur + 4, dB + cur + 256);
                wgmma_commit();
                if (t + 1 < TAIL_LEAD) { G2_NEXT(); mbar_wait(sb + GOK + 8 * s, ph); }
                wgmma_fence();
                wgmma_n128(accS, dS + cur + 6, dB + cur + 384);
                wgmma_commit();
            }
#undef G2_NEXT
            const uint32_t rx = sb + OFF_RX + w * 4096 + lane * 16;
            const uint32_t dst = mapa(rx, rank ^ 1), bar = mapa(sb + RXFULL + 8 * w, rank ^ 1);
            mbar_wait(sb + TXOK, 0);
            wgmma_fence();
            wgmma_n128(accK, dK + offs[0], dB + offs[0]);
            wgmma_n128(accK, dK + offs[0] + 2, dB + offs[0] + 128);
            wgmma_commit();
            wgmma_wait<1>();
            fence_regs(accS);
            uint32_t v[8][4];
            const int orow = __shfl_sync(0xffffffffu, 128 * rb + 64 * rank + 16 * w, 0);
#pragma unroll
            for (int m = 2; m < 4 * TAIL_LEAD; m++) {
                if (m < 10) {
                    const float* o = &accS[8 * (m - 2)];
                    asm volatile("st.async.weak.shared::cluster.mbarrier::complete_tx::bytes.v4.b32 [%0], {%1,%2,%3,%4}, [%5];"
                                 ::"r"(dst + (m - 2) * 512), "r"(pack2(o[0], o[1])), "r"(pack2(o[2], o[3])), "r"(pack2(o[4], o[5])),
                                   "r"(pack2(o[6], o[7])), "r"(bar) : "memory");
                }
                if (m == 4 * TAIL_LEAD - 1) {
                    mbar_wait(sb + RXFULL + 8 * w, 0);
#pragma unroll
                    for (int i = 0; i < 8; i++)
                        asm volatile("ld.shared.v4.u32 {%0,%1,%2,%3}, [%4];" : "=r"(v[i][0]), "=r"(v[i][1]), "=r"(v[i][2]), "=r"(v[i][3]) : "r"(rx + i * 512) : "memory");
                }
                wgmma_fence();
                wgmma_n128(accK, dK + offs[m >> 2] + 2 * (m & 3), dB + offs[m >> 2] + 128 * (m & 3));
                wgmma_commit();
            }
            __syncwarp();
            wgmma_wait<0>();
            fence_regs(accK);
            const uint32_t ob = sb + OFF_RX + w * 4096 + (uint32_t)(lane & 15) * 128;
#pragma unroll
            for (int jp = 0; jp < 8; jp++) {
                const float* o = &accK[8 * jp];
                uint32_t r[4];
#pragma unroll
                for (int i = 0; i < 4; i++)
                    asm("add.rn.bf16x2 %0, %1, %2;" : "=r"(r[i]) : "r"(pack2(o[2 * i], o[2 * i + 1])), "r"(v[jp][i]));
                stsm_x4(ob + (jp >> 2) * 2048 + (((2 * (jp & 3) + st_hi) ^ st_sw) << 4), r[0], r[1], r[2], r[3]);
            }
            asm volatile("fence.proxy.async.shared::cta;" ::: "memory");
            __syncwarp();
            if (elect_one()) {
                tma_store_3d(&p.out, sb + OFF_RX + w * 4096, 0, orow, 2 * ct);
                asm volatile("cp.async.bulk.commit_group;" ::: "memory");
                asm volatile("cp.async.bulk.wait_group.read 0;" ::: "memory");
            }
        }
    }
}

typedef CUresult (*EncodeFn)(CUtensorMap*, CUtensorMapDataType, cuuint32_t, void*, const cuuint64_t*, const cuuint64_t*,
                             const cuuint32_t*, const cuuint32_t*, CUtensorMapInterleave, CUtensorMapSwizzle,
                             CUtensorMapL2promotion, CUtensorMapFloatOOBfill);

void make_2d(EncodeFn enc, CUtensorMap* m, const void* ptr, uint64_t rows, uint64_t cols, uint32_t brows) {
    cuuint64_t dims[2] = {cols, rows};
    cuuint64_t strides[1] = {cols * 2};
    cuuint32_t box[2] = {64, brows};
    cuuint32_t es[2] = {1, 1};
    CUresult r = enc(m, CU_TENSOR_MAP_DATA_TYPE_BFLOAT16, 2, const_cast<void*>(ptr), dims, strides, box, es,
                     CU_TENSOR_MAP_INTERLEAVE_NONE, CU_TENSOR_MAP_SWIZZLE_128B, CU_TENSOR_MAP_L2_PROMOTION_L2_256B,
                     CU_TENSOR_MAP_FLOAT_OOB_FILL_NONE);
    if (r != CUDA_SUCCESS) fprintf(stderr, "tensor map 2d failed: %d\n", (int)r);
}
void make_3d(EncodeFn enc, CUtensorMap* m, const void* ptr, uint64_t rows, uint64_t cols, uint32_t brows) {
    cuuint64_t dims[3] = {64, rows, cols / 64};
    cuuint64_t strides[2] = {cols * 2, 128};
    cuuint32_t box[3] = {64, brows, 2};
    cuuint32_t es[3] = {1, 1, 1};
    CUresult r = enc(m, CU_TENSOR_MAP_DATA_TYPE_BFLOAT16, 3, const_cast<void*>(ptr), dims, strides, box, es,
                     CU_TENSOR_MAP_INTERLEAVE_NONE, CU_TENSOR_MAP_SWIZZLE_128B, CU_TENSOR_MAP_L2_PROMOTION_L2_256B,
                     CU_TENSOR_MAP_FLOAT_OOB_FILL_NONE);
    if (r != CUDA_SUCCESS) fprintf(stderr, "tensor map 3d failed: %d\n", (int)r);
}

}

extern "C" void kernel_launch(void* const* d_in, const int* in_sizes, int n_in, void* d_out, int out_size) {
    (void)in_sizes; (void)n_in; (void)out_size;
    static EncodeFn enc = nullptr;
    if (!enc) {
        void* fn = nullptr;
        cudaDriverEntryPointQueryResult qr;
        cudaGetDriverEntryPoint("cuTensorMapEncodeTiled", &fn, cudaEnableDefault, &qr);
        enc = (EncodeFn)fn;
        cudaFuncSetAttribute(fused_kernel, cudaFuncAttributeMaxDynamicSharedMemorySize, SMEM_BYTES);
    }
    Params p;
    make_2d(enc, &p.x, d_in[0], SEQ, DM, 128);
    make_2d(enc, &p.qkv, d_in[1], DM, 3 * DM, 64);
    make_3d(enc, &p.wo, d_in[2], DM, DM, 64);
    make_2d(enc, &p.wg, d_in[4], DM, FF, 64);
    make_2d(enc, &p.wu, d_in[5], DM, FF, 64);
    make_3d(enc, &p.wd, d_in[6], FF, DM, 64);
    make_3d(enc, &p.out, d_out, SEQ, DM, 16);
    p.gate_w = (const __nv_bfloat16*)d_in[7];
    p.xp = (const __nv_bfloat16*)d_in[0];
    p.wqkv = (const __nv_bfloat16*)d_in[1];
    fused_kernel<<<128, 384, SMEM_BYTES, cudaStreamPerThread>>>(p);
}
```
